```python
import torch

def _softmax(x, axis=-1):
    return torch.softmax(x, dim=axis)
def _gelu(x):
    return torch.nn.functional.gelu(x, approximate="tanh")
def _silu(x):
    return torch.nn.functional.silu(x)
def _sigmoid(x):
    return torch.sigmoid(x)
def _layernorm(x, axis=-1, eps=1e-5):
    m = x.mean(dim=axis, keepdim=True)
    v = x.var(dim=axis, keepdim=True, unbiased=False)
    return (x - m) / torch.sqrt(v + eps)
def _scatter_add(tgt, idx, src, axis=0):
    return tgt.clone().index_add_(axis, idx, src)
def _segment_sum(src, seg, n):
    out = torch.zeros((n,) + src.shape[1:], dtype=src.dtype)
    return out.index_add_(0, seg, src)
def _pad(x, pw):
    flat = tuple(v for pair in reversed(pw) for v in pair)
    return torch.nn.functional.pad(x, flat)

kernel_name = 'sequential_preLN__gqa_block_cached__dense_activation_gelu__decode'

def setup_inputs():

    _w = (lambda a: (lambda t: t.to(torch.bfloat16) if t.is_floating_point() else t)(torch.as_tensor(a)))
    def _A_setup():
        B, Sq, D = 2, 1, 512
        Hq, Hkv, Sk, Dh = 32, 8, 8192, 128
        assert Hq % Hkv == 0, (Hq, Hkv)
        return {
            "x": _w((lambda *s: torch.randn(*s, dtype=torch.bfloat16) * 0.05)(B, Sq, D)),
            "k_cache": _w((lambda *s: torch.randn(*s, dtype=torch.bfloat16) * 3.2)(B, Hkv, Sk, Dh)),
            "v_cache": _w((lambda *s: torch.randn(*s, dtype=torch.bfloat16) * 0.8)(B, Hkv, Sk, Dh)),
            "wq": _w((lambda *s: torch.randn(*s, dtype=torch.bfloat16) * 3.2)(D, Hq * Dh) * (D ** -0.5)),
            "wo": _w((lambda *s: torch.randn(*s, dtype=torch.bfloat16) * 0.8)(Hq * Dh, D) * ((Hq * Dh) ** -0.5)),
        }
    _A_in = _A_setup()

    def _B_setup():
        B, S, D, F = 2, 1, 512, 1792
        return {
            "x": _w((lambda *s: torch.randn(*s, dtype=torch.bfloat16) * 0.05)(B, S, D)),
            "w1": _w((lambda *s: torch.randn(*s, dtype=torch.bfloat16) * 3.2)(D, F) * (D ** -0.5)),
            "b1": _w((lambda *s: torch.randn(*s, dtype=torch.bfloat16) * 3.2)(F) * 0.01),
            "w2": _w((lambda *s: torch.randn(*s, dtype=torch.bfloat16) * 0.8)(F, D) * (F ** -0.5)),
            "b2": _w((lambda *s: torch.randn(*s, dtype=torch.bfloat16) * 0.8)(D) * 0.01),
        }
    _B_in = _B_setup()

    return {
        "A_x": _A_in["x"],
        "A_k_cache": _A_in["k_cache"],
        "A_v_cache": _A_in["v_cache"],
        "A_wq": _A_in["wq"],
        "A_wo": _A_in["wo"],
        "B_x": _B_in["x"],
        "B_w1": _B_in["w1"],
        "B_b1": _B_in["b1"],
        "B_w2": _B_in["w2"],
        "B_b2": _B_in["b2"],
    }

def reference(A_x, A_k_cache, A_v_cache, A_wq, A_wo, B_x, B_w1, B_b1, B_w2, B_b2):
    def _A_ref(x, k_cache, v_cache, wq, wo):
        B, Sq, D = x.shape
        Hq, Dh = 32, 128
        Hkv = k_cache.shape[1]
        rep = Hq // Hkv
        q = (lambda x, *d: x.permute(*d))((x @ wq).reshape(B, Sq, Hq, Dh), 0, 2, 1, 3)
        k = (lambda x, n, axis: torch.repeat_interleave(x, n, dim=axis))(k_cache, rep, axis=1)
        v = (lambda x, n, axis: torch.repeat_interleave(x, n, dim=axis))(v_cache, rep, axis=1)
        scores = torch.einsum("bhqd,bhkd->bhqk", q, k) * (Dh ** -0.5)
        p = _softmax(scores, axis=-1)
        o = torch.einsum("bhqk,bhkd->bhqd", p, v)
        return (lambda x, *d: x.permute(*d))(o, 0, 2, 1, 3).reshape(B, Sq, Hq * Dh) @ wo

    def _B_ref(x, w1, b1, w2, b2):
        h = torch.einsum("bsd,df->bsf", x, w1) + b1
        h = _gelu(h)
        return torch.einsum("bsf,fd->bsd", h, w2) + b2

    x = A_x
    h = x + _A_ref(_layernorm(x, axis=-1), A_k_cache, A_v_cache, A_wq, A_wo)
    h2 = h + _B_ref(_layernorm(h, axis=-1), B_w1, B_b1, B_w2, B_b2)
    return h2
```

```cpp
#include <cuda_runtime.h>
#include <cuda_bf16.h>
#include <cuda.h>
#include <stdint.h>

namespace {

constexpr int NB = 2, DM = 512, HQ = 32, HKV = 8, SK = 8192, DH = 128, FF = 1792;
constexpr int NCTA = 128, NSPLIT = 8, KEYS_PER_CTA = SK / NSPLIT;
constexpr int NWARP = 8, NTHREADS = NWARP * 32;
constexpr int NSTAGE = 3;
constexpr int STAGE_BYTES = 8192;
constexpr int NBLK = KEYS_PER_CTA / (16 * NWARP);
constexpr int RING_BYTES = NWARP * NSTAGE * STAGE_BYTES;
constexpr int SMEM_BYTES = RING_BYTES + 4096 + 1024 + 1024;

__device__ __nv_bfloat16 g_q[NB * HQ * DH];
__device__ float g_pm[16 * NSPLIT * 4];
__device__ float g_pl[16 * NSPLIT * 4];
__device__ float g_po[16 * NSPLIT * 4 * DH];
__device__ float g_attn_acc[NB * DM];
__device__ float g_out_acc[NB * DM];
__device__ unsigned g_bar;
__device__ unsigned g_done;

__device__ __forceinline__ uint32_t smem_u32(const void* p) {
    return (uint32_t)__cvta_generic_to_shared(p);
}
__device__ __forceinline__ float bf16r(float x) {
    return __bfloat162float(__float2bfloat16_rn(x));
}
__device__ __forceinline__ uint32_t pack_bf16(float lo, float hi) {
    __nv_bfloat162 v = __floats2bfloat162_rn(lo, hi);
    return *reinterpret_cast<uint32_t*>(&v);
}
__device__ __forceinline__ float bf_lo(uint32_t v) { return __uint_as_float(v << 16); }
__device__ __forceinline__ float bf_hi(uint32_t v) { return __uint_as_float(v & 0xffff0000u); }

__device__ __forceinline__ void mbar_init(uint32_t bar, uint32_t cnt) {
    asm volatile("mbarrier.init.shared::cta.b64 [%0], %1;" ::"r"(bar), "r"(cnt) : "memory");
}
__device__ __forceinline__ void mbar_expect_tx(uint32_t bar, uint32_t bytes) {
    asm volatile("mbarrier.arrive.expect_tx.shared::cta.b64 _, [%0], %1;" ::"r"(bar), "r"(bytes) : "memory");
}
__device__ __forceinline__ void mbar_wait(uint32_t bar, uint32_t parity) {
    asm volatile(
        "{\n"
        ".reg .pred p;\n"
        "WAIT_LOOP:\n"
        "mbarrier.try_wait.parity.shared::cta.b64 p, [%0], %1;\n"
        "@p bra WAIT_DONE;\n"
        "bra WAIT_LOOP;\n"
        "WAIT_DONE:\n"
        "}\n" ::"r"(bar), "r"(parity) : "memory");
}
__device__ __forceinline__ void tma_2d(uint32_t dst, const CUtensorMap* map, uint32_t bar, int c0, int c1) {
    asm volatile(
        "cp.async.bulk.tensor.2d.shared::cluster.global.mbarrier::complete_tx::bytes [%0], [%1, {%3, %4}], [%2];"
        ::"r"(dst), "l"(map), "r"(bar), "r"(c0), "r"(c1) : "memory");
}
__device__ __forceinline__ void ldsm_x4(uint32_t addr, uint32_t& r0, uint32_t& r1, uint32_t& r2, uint32_t& r3) {
    asm volatile("ldmatrix.sync.aligned.m8n8.x4.shared.b16 {%0,%1,%2,%3}, [%4];"
                 : "=r"(r0), "=r"(r1), "=r"(r2), "=r"(r3) : "r"(addr) : "memory");
}
__device__ __forceinline__ void ldsm_x4_t(uint32_t addr, uint32_t& r0, uint32_t& r1, uint32_t& r2, uint32_t& r3) {
    asm volatile("ldmatrix.sync.aligned.m8n8.x4.trans.shared.b16 {%0,%1,%2,%3}, [%4];"
                 : "=r"(r0), "=r"(r1), "=r"(r2), "=r"(r3) : "r"(addr) : "memory");
}
__device__ __forceinline__ void mma16816(float* c, uint32_t a0, uint32_t a1, uint32_t a2, uint32_t a3,
                                         uint32_t b0, uint32_t b1) {
    asm volatile(
        "mma.sync.aligned.m16n8k16.row.col.f32.bf16.bf16.f32 {%0,%1,%2,%3}, {%4,%5,%6,%7}, {%8,%9}, {%0,%1,%2,%3};"
        : "+f"(c[0]), "+f"(c[1]), "+f"(c[2]), "+f"(c[3])
        : "r"(a0), "r"(a1), "r"(a2), "r"(a3), "r"(b0), "r"(b1));
}
__device__ __forceinline__ unsigned ld_acquire(const unsigned* p) {
    unsigned v;
    asm volatile("ld.acquire.gpu.global.u32 %0, [%1];" : "=r"(v) : "l"(p) : "memory");
    return v;
}
__device__ __forceinline__ uint4 ldg_nc_v4(const void* p) {
    uint4 v;
    asm volatile("ld.global.nc.L1::no_allocate.v4.u32 {%0,%1,%2,%3}, [%4];"
                 : "=r"(v.x), "=r"(v.y), "=r"(v.z), "=r"(v.w) : "l"(p));
    return v;
}
__device__ __forceinline__ uint32_t ldg_nc_u32(const void* p) {
    uint32_t v;
    asm volatile("ld.global.nc.L1::no_allocate.u32 %0, [%1];" : "=r"(v) : "l"(p));
    return v;
}

__device__ __forceinline__ void grid_barrier() {
    __syncthreads();
    if (threadIdx.x == 0) {
        __threadfence();
        unsigned old = atomicAdd(&g_bar, 1u);
        unsigned target = (old / NCTA + 1u) * NCTA;
        unsigned iters = 0;
        while ((int)(ld_acquire(&g_bar) - target) < 0) {
            if (++iters > 20000000u) break;
        }
        __threadfence();
    }
    __syncthreads();
}

__device__ __forceinline__ void layernorm_2x512(float* v, float* red, int tid) {
    int warp = tid >> 5, lane = tid & 31;
    float a0 = v[2 * tid], a1 = v[2 * tid + 1], b0 = v[512 + 2 * tid], b1 = v[512 + 2 * tid + 1];
    float sa = a0 + a1, sb = b0 + b1;
#pragma unroll
    for (int o = 16; o > 0; o >>= 1) {
        sa += __shfl_xor_sync(0xffffffffu, sa, o);
        sb += __shfl_xor_sync(0xffffffffu, sb, o);
    }
    if (lane == 0) { red[warp] = sa; red[8 + warp] = sb; }
    __syncthreads();
    float ma = 0.f, mb = 0.f;
#pragma unroll
    for (int w = 0; w < 8; w++) { ma += red[w]; mb += red[8 + w]; }
    ma *= (1.f / 512.f); mb *= (1.f / 512.f);
    float da0 = a0 - ma, da1 = a1 - ma, db0 = b0 - mb, db1 = b1 - mb;
    float va = da0 * da0 + da1 * da1, vb = db0 * db0 + db1 * db1;
#pragma unroll
    for (int o = 16; o > 0; o >>= 1) {
        va += __shfl_xor_sync(0xffffffffu, va, o);
        vb += __shfl_xor_sync(0xffffffffu, vb, o);
    }
    __syncthreads();
    if (lane == 0) { red[16 + warp] = va; red[24 + warp] = vb; }
    __syncthreads();
    va = 0.f; vb = 0.f;
#pragma unroll
    for (int w = 0; w < 8; w++) { va += red[16 + w]; vb += red[24 + w]; }
    va = bf16r(va * (1.f / 512.f)); vb = bf16r(vb * (1.f / 512.f));
    float mra = bf16r(ma), mrb = bf16r(mb);
    float sda = bf16r(sqrtf(bf16r(va + 1e-5f))), sdb = bf16r(sqrtf(bf16r(vb + 1e-5f)));
    v[2 * tid] = bf16r(bf16r(a0 - mra) / sda);
    v[2 * tid + 1] = bf16r(bf16r(a1 - mra) / sda);
    v[512 + 2 * tid] = bf16r(bf16r(b0 - mrb) / sdb);
    v[512 + 2 * tid + 1] = bf16r(bf16r(b1 - mrb) / sdb);
    __syncthreads();
}

__device__ __forceinline__ float gelu_tanh(float x) {
    const float k0 = 0.7978845608028654f, k1 = 0.044715f;
    float inner = k0 * (x + k1 * x * x * x);
    return 0.5f * x * (1.f + tanhf(inner));
}

__global__ void __launch_bounds__(NTHREADS, 1)
fused_kernel(const __grid_constant__ CUtensorMap mapK, const __grid_constant__ CUtensorMap mapV,
             const __nv_bfloat16* __restrict__ x, const __nv_bfloat16* __restrict__ wq,
             const __nv_bfloat16* __restrict__ wo, const __nv_bfloat16* __restrict__ w1,
             const __nv_bfloat16* __restrict__ b1, const __nv_bfloat16* __restrict__ w2,
             const __nv_bfloat16* __restrict__ b2, __nv_bfloat16* __restrict__ out) {
    extern __shared__ __align__(1024) uint8_t smem_raw[];
    uint8_t* smem = smem_raw + ((1024u - (smem_u32(smem_raw) & 1023u)) & 1023u);
    uint8_t* ring = smem;
    uint64_t* bars = reinterpret_cast<uint64_t*>(smem + RING_BYTES);
    float* s_vec = reinterpret_cast<float*>(smem + RING_BYTES + 256);
    float* s_red = reinterpret_cast<float*>(smem + RING_BYTES + 256 + 4096);
    float* s_o = s_red + 64;
    float* s_f = s_o + 64;

    const int tid = threadIdx.x, warp = tid >> 5, lane = tid & 31;
    const int cta = blockIdx.x;
    const int bh = cta >> 3, split = cta & 7;
    const int b = bh >> 3, kvh = bh & 7;

    const uint32_t ring_w = smem_u32(ring) + warp * (NSTAGE * STAGE_BYTES);
    const uint32_t bar_w = smem_u32(bars) + warp * (NSTAGE * 8);
    if (lane == 0) {
#pragma unroll
        for (int s = 0; s < NSTAGE; s++) mbar_init(bar_w + s * 8, 1);
        asm volatile("fence.mbarrier_init.release.cluster;" ::: "memory");
    }
    __syncwarp();

    uint32_t xv0 = ldg_nc_u32(x + 2 * tid);
    uint32_t xv1 = ldg_nc_u32(x + 512 + 2 * tid);
    uint4 wqv[8];
    {
        const __nv_bfloat16* p = wq + (size_t)(tid >> 2) * (HQ * DH) + cta * 32 + (tid & 3) * 8;
#pragma unroll
        for (int i = 0; i < 8; i++) wqv[i] = ldg_nc_v4(p + (size_t)i * 64 * (HQ * DH));
    }
    const int row0 = bh * SK + split * KEYS_PER_CTA + warp * 16;
    if (lane == 0) {
#pragma unroll
        for (int s = 0; s < NSTAGE; s++) {
            uint32_t dst = ring_w + s * STAGE_BYTES;
            uint32_t bar = bar_w + s * 8;
            int r = row0 + s * 128;
            mbar_expect_tx(bar, STAGE_BYTES);
            tma_2d(dst, &mapK, bar, 0, r);
            tma_2d(dst + 2048, &mapK, bar, 64, r);
            tma_2d(dst + 4096, &mapV, bar, 0, r);
            tma_2d(dst + 6144, &mapV, bar, 64, r);
        }
    }
    uint32_t wov[32];
    {
        const __nv_bfloat16* p = wo + (size_t)(cta * 32) * DM + 2 * tid;
#pragma unroll
        for (int r = 0; r < 32; r++) wov[r] = ldg_nc_u32(p + (size_t)r * DM);
    }
    uint32_t w1v[14];
    {
        const __nv_bfloat16* p = w1 + (size_t)(2 * tid) * FF + cta * 14;
#pragma unroll
        for (int i = 0; i < 7; i++) w1v[i] = ldg_nc_u32(p + 2 * i);
#pragma unroll
        for (int i = 0; i < 7; i++) w1v[7 + i] = ldg_nc_u32(p + FF + 2 * i);
    }
    uint32_t w2v[14];
    {
        const __nv_bfloat16* p = w2 + (size_t)(cta * 14) * DM + 2 * tid;
#pragma unroll
        for (int r = 0; r < 14; r++) w2v[r] = ldg_nc_u32(p + (size_t)r * DM);
    }

    s_vec[2 * tid] = bf_lo(xv0); s_vec[2 * tid + 1] = bf_hi(xv0);
    s_vec[512 + 2 * tid] = bf_lo(xv1); s_vec[512 + 2 * tid + 1] = bf_hi(xv1);
    __syncthreads();
    layernorm_2x512(s_vec, s_red, tid);

    {
        float acc[2][8];
#pragma unroll
        for (int i = 0; i < 8; i++) { acc[0][i] = 0.f; acc[1][i] = 0.f; }
#pragma unroll
        for (int i = 0; i < 8; i++) {
            int r = (tid >> 2) + i * 64;
            float x0 = s_vec[r], x1 = s_vec[512 + r];
            uint32_t w[4] = {wqv[i].x, wqv[i].y, wqv[i].z, wqv[i].w};
#pragma unroll
            for (int j = 0; j < 4; j++) {
                float lo = bf_lo(w[j]), hi = bf_hi(w[j]);
                acc[0][2 * j] += x0 * lo; acc[0][2 * j + 1] += x0 * hi;
                acc[1][2 * j] += x1 * lo; acc[1][2 * j + 1] += x1 * hi;
            }
        }
#pragma unroll
        for (int o = 4; o < 32; o <<= 1) {
#pragma unroll
            for (int i = 0; i < 8; i++) {
                acc[0][i] += __shfl_xor_sync(0xffffffffu, acc[0][i], o);
                acc[1][i] += __shfl_xor_sync(0xffffffffu, acc[1][i], o);
            }
        }
        __shared__ float s_qpart[NWARP][2][32];
        if (lane < 4) {
#pragma unroll
            for (int i = 0; i < 8; i++) {
                s_qpart[warp][0][lane * 8 + i] = acc[0][i];
                s_qpart[warp][1][lane * 8 + i] = acc[1][i];
            }
        }
        __syncthreads();
        if (tid < 64) {
            int bb = tid >> 5, c = tid & 31;
            float s = 0.f;
#pragma unroll
            for (int w = 0; w < NWARP; w++) s += s_qpart[w][bb][c];
            g_q[bb * (HQ * DH) + cta * 32 + c] = __float2bfloat16_rn(s);
        }
        if (cta == 0) {
            for (int i = tid; i < NB * DM; i += NTHREADS) { g_attn_acc[i] = 0.f; g_out_acc[i] = 0.f; }
        }
    }
    grid_barrier();

    uint32_t qa[8][2];
    {
        int hl = lane >> 2;
        const __nv_bfloat16* qp = g_q + b * (HQ * DH) + (kvh * 4 + (hl & 3)) * DH + (lane & 3) * 2;
#pragma unroll
        for (int ks = 0; ks < 8; ks++) {
            uint32_t v0 = __ldcg(reinterpret_cast<const unsigned*>(qp + ks * 16));
            uint32_t v1 = __ldcg(reinterpret_cast<const unsigned*>(qp + ks * 16 + 8));
            qa[ks][0] = hl < 4 ? v0 : 0u;
            qa[ks][1] = hl < 4 ? v1 : 0u;
        }
    }

    float oacc[16][4];
#pragma unroll
    for (int j = 0; j < 16; j++) { oacc[j][0] = 0.f; oacc[j][1] = 0.f; oacc[j][2] = 0.f; oacc[j][3] = 0.f; }
    float m_run = -INFINITY, l_run = 0.f;
    const float scale = 0.08838834764831845f;
    const float LOG2E = 1.4426950408889634f;

    const int lrow = lane & 7, lmat = lane >> 3;
    const int k_row = (lmat >> 1) * 8 + lrow;
    const int k_cofs = lmat & 1;
    const int v_row = (lmat & 1) * 8 + lrow;
    const int v_cofs = lmat >> 1;

#pragma unroll 1
    for (int it = 0; it < NBLK; it++) {
        const int s = it % NSTAGE;
        const uint32_t parity = (it / NSTAGE) & 1;
        const uint32_t st = ring_w + s * STAGE_BYTES;
        mbar_wait(bar_w + s * 8, parity);

        float sc[2][4];
#pragma unroll
        for (int j = 0; j < 2; j++) { sc[j][0] = 0.f; sc[j][1] = 0.f; sc[j][2] = 0.f; sc[j][3] = 0.f; }
#pragma unroll
        for (int ks = 0; ks < 8; ks++) {
            int chunk = (ks & 3) * 2 + k_cofs;
            uint32_t addr = st + (ks >> 2) * 2048 + k_row * 128 + ((chunk ^ (k_row & 7)) << 4);
            uint32_t r0, r1, r2, r3;
            ldsm_x4(addr, r0, r1, r2, r3);
            mma16816(sc[0], qa[ks][0], 0u, qa[ks][1], 0u, r0, r1);
            mma16816(sc[1], qa[ks][0], 0u, qa[ks][1], 0u, r2, r3);
        }
        float v00 = bf16r(bf16r(sc[0][0]) * scale), v01 = bf16r(bf16r(sc[0][1]) * scale);
        float v10 = bf16r(bf16r(sc[1][0]) * scale), v11 = bf16r(bf16r(sc[1][1]) * scale);
        float mx = fmaxf(fmaxf(v00, v01), fmaxf(v10, v11));
        mx = fmaxf(mx, __shfl_xor_sync(0xffffffffu, mx, 1));
        mx = fmaxf(mx, __shfl_xor_sync(0xffffffffu, mx, 2));
        float m_new = fmaxf(m_run, mx);
        float corr = exp2f((m_run - m_new) * LOG2E);
        float p00 = exp2f((v00 - m_new) * LOG2E), p01 = exp2f((v01 - m_new) * LOG2E);
        float p10 = exp2f((v10 - m_new) * LOG2E), p11 = exp2f((v11 - m_new) * LOG2E);
        l_run = l_run * corr + (p00 + p01 + p10 + p11);
        m_run = m_new;
        uint32_t pa0 = pack_bf16(p00, p01), pa2 = pack_bf16(p10, p11);
#pragma unroll
        for (int j = 0; j < 16; j++) { oacc[j][0] *= corr; oacc[j][1] *= corr; }
#pragma unroll
        for (int jj = 0; jj < 8; jj++) {
            int chunk = (jj & 3) * 2 + v_cofs;
            uint32_t addr = st + 4096 + (jj >> 2) * 2048 + v_row * 128 + ((chunk ^ (v_row & 7)) << 4);
            uint32_t r0, r1, r2, r3;
            ldsm_x4_t(addr, r0, r1, r2, r3);
            mma16816(oacc[2 * jj], pa0, 0u, pa2, 0u, r0, r1);
            mma16816(oacc[2 * jj + 1], pa0, 0u, pa2, 0u, r2, r3);
        }
        __syncwarp();
        if (lane == 0 && it + NSTAGE < NBLK) {
            uint32_t bar = bar_w + s * 8;
            int r = row0 + (it + NSTAGE) * 128;
            mbar_expect_tx(bar, STAGE_BYTES);
            tma_2d(st, &mapK, bar, 0, r);
            tma_2d(st + 2048, &mapK, bar, 64, r);
            tma_2d(st + 4096, &mapV, bar, 0, r);
            tma_2d(st + 6144, &mapV, bar, 64, r);
        }
    }
    l_run += __shfl_xor_sync(0xffffffffu, l_run, 1);
    l_run += __shfl_xor_sync(0xffffffffu, l_run, 2);

    __syncthreads();
    float* r_o = reinterpret_cast<float*>(ring);
    float* r_m = reinterpret_cast<float*>(ring + 16384);
    float* r_l = r_m + 32;
    if (lane < 16) {
        int hl = lane >> 2;
#pragma unroll
        for (int j = 0; j < 16; j++) {
            float2 v = make_float2(oacc[j][0], oacc[j][1]);
            *reinterpret_cast<float2*>(&r_o[(warp * 4 + hl) * DH + j * 8 + (lane & 3) * 2]) = v;
        }
        if ((lane & 3) == 0) { r_m[warp * 4 + hl] = m_run; r_l[warp * 4 + hl] = l_run; }
    }
    __syncthreads();
    {
        int hl = tid >> 6, d = (tid & 63) * 2;
        float mm = -INFINITY;
#pragma unroll
        for (int w = 0; w < NWARP; w++) mm = fmaxf(mm, r_m[w * 4 + hl]);
        float o0 = 0.f, o1 = 0.f, ll = 0.f;
#pragma unroll
        for (int w = 0; w < NWARP; w++) {
            float c = exp2f((r_m[w * 4 + hl] - mm) * LOG2E);
            float2 v = *reinterpret_cast<float2*>(&r_o[(w * 4 + hl) * DH + d]);
            o0 += c * v.x; o1 += c * v.y; ll += c * r_l[w * 4 + hl];
        }
        int pidx = (cta * 4 + hl);
        *reinterpret_cast<float2*>(&g_po[(size_t)pidx * DH + d]) = make_float2(o0, o1);
        if ((tid & 63) == 0) { g_pm[pidx] = mm; g_pl[pidx] = ll; }
    }
    grid_barrier();

    {
        int head = cta >> 2, dq = (cta & 3) * 32;
        int kv = head >> 2, hl = head & 3;
        if (tid < 64) {
            int bb = tid >> 5, d = tid & 31;
            int base = ((bb * 8 + kv) * NSPLIT) * 4 + hl;
            float pm[NSPLIT], pl[NSPLIT], po[NSPLIT];
#pragma unroll
            for (int s = 0; s < NSPLIT; s++) {
                pm[s] = __ldcg(&g_pm[base + s * 4]);
                pl[s] = __ldcg(&g_pl[base + s * 4]);
                po[s] = __ldcg(&g_po[(size_t)(base + s * 4) * DH + dq + d]);
            }
            float mm = -INFINITY;
#pragma unroll
            for (int s = 0; s < NSPLIT; s++) mm = fmaxf(mm, pm[s]);
            float oo = 0.f, ll = 0.f;
#pragma unroll
            for (int s = 0; s < NSPLIT; s++) {
                float c = exp2f((pm[s] - mm) * LOG2E);
                oo += c * po[s]; ll += c * pl[s];
            }
            s_o[tid] = bf16r(oo / ll);
        }
        __syncthreads();
        float a00 = 0.f, a01 = 0.f, a10 = 0.f, a11 = 0.f;
#pragma unroll
        for (int r = 0; r < 32; r++) {
            float o0 = s_o[r], o1 = s_o[32 + r];
            float lo = bf_lo(wov[r]), hi = bf_hi(wov[r]);
            a00 += o0 * lo; a01 += o0 * hi; a10 += o1 * lo; a11 += o1 * hi;
        }
        atomicAdd(&g_attn_acc[2 * tid], a00);
        atomicAdd(&g_attn_acc[2 * tid + 1], a01);
        atomicAdd(&g_attn_acc[512 + 2 * tid], a10);
        atomicAdd(&g_attn_acc[512 + 2 * tid + 1], a11);
    }
    grid_barrier();

    float h00, h01, h10, h11;
    {
        float2 aa = __ldcg(reinterpret_cast<const float2*>(&g_attn_acc[2 * tid]));
        float2 ab = __ldcg(reinterpret_cast<const float2*>(&g_attn_acc[512 + 2 * tid]));
        h00 = bf16r(bf_lo(xv0) + bf16r(aa.x)); h01 = bf16r(bf_hi(xv0) + bf16r(aa.y));
        h10 = bf16r(bf_lo(xv1) + bf16r(ab.x)); h11 = bf16r(bf_hi(xv1) + bf16r(ab.y));
        s_vec[2 * tid] = h00; s_vec[2 * tid + 1] = h01;
        s_vec[512 + 2 * tid] = h10; s_vec[512 + 2 * tid + 1] = h11;
        __syncthreads();
        layernorm_2x512(s_vec, s_red, tid);
        float n00 = s_vec[2 * tid], n01 = s_vec[2 * tid + 1];
        float n10 = s_vec[512 + 2 * tid], n11 = s_vec[512 + 2 * tid + 1];
        float f[2][14];
#pragma unroll
        for (int i = 0; i < 7; i++) {
            float lo0 = bf_lo(w1v[i]), hi0 = bf_hi(w1v[i]);
            float lo1 = bf_lo(w1v[7 + i]), hi1 = bf_hi(w1v[7 + i]);
            f[0][2 * i] = n00 * lo0 + n01 * lo1; f[0][2 * i + 1] = n00 * hi0 + n01 * hi1;
            f[1][2 * i] = n10 * lo0 + n11 * lo1; f[1][2 * i + 1] = n10 * hi0 + n11 * hi1;
        }
#pragma unroll
        for (int o = 16; o > 0; o >>= 1) {
#pragma unroll
            for (int i = 0; i < 14; i++) {
                f[0][i] += __shfl_xor_sync(0xffffffffu, f[0][i], o);
                f[1][i] += __shfl_xor_sync(0xffffffffu, f[1][i], o);
            }
        }
        float* s_fp = reinterpret_cast<float*>(ring);
        if (lane == 0) {
#pragma unroll
            for (int i = 0; i < 14; i++) { s_fp[warp * 28 + i] = f[0][i]; s_fp[warp * 28 + 14 + i] = f[1][i]; }
        }
        __syncthreads();
        if (tid < 28) {
            float s = 0.f;
#pragma unroll
            for (int w = 0; w < NWARP; w++) s += s_fp[w * 28 + tid];
            int c = tid % 14;
            float bias = __bfloat162float(b1[cta * 14 + c]);
            float hh = bf16r(bf16r(s) + bias);
            s_f[tid] = bf16r(gelu_tanh(hh));
        }
        __syncthreads();
        float a00 = 0.f, a01 = 0.f, a10 = 0.f, a11 = 0.f;
#pragma unroll
        for (int r = 0; r < 14; r++) {
            float f0 = s_f[r], f1 = s_f[14 + r];
            float lo = bf_lo(w2v[r]), hi = bf_hi(w2v[r]);
            a00 += f0 * lo; a01 += f0 * hi; a10 += f1 * lo; a11 += f1 * hi;
        }
        atomicAdd(&g_out_acc[2 * tid], a00);
        atomicAdd(&g_out_acc[2 * tid + 1], a01);
        atomicAdd(&g_out_acc[512 + 2 * tid], a10);
        atomicAdd(&g_out_acc[512 + 2 * tid + 1], a11);
    }
    __shared__ unsigned s_last;
    __syncthreads();
    if (tid == 0) {
        __threadfence();
        unsigned old = atomicAdd(&g_done, 1u);
        s_last = ((old % NCTA) == NCTA - 1) ? 1u : 0u;
        __threadfence();
    }
    __syncthreads();
    if (s_last) {
        float2 oa = __ldcg(reinterpret_cast<const float2*>(&g_out_acc[2 * tid]));
        float2 ob = __ldcg(reinterpret_cast<const float2*>(&g_out_acc[512 + 2 * tid]));
        uint32_t bb = *reinterpret_cast<const uint32_t*>(b2 + 2 * tid);
        float bl = bf_lo(bb), bhh = bf_hi(bb);
        float r00 = h00 + bf16r(bf16r(oa.x) + bl), r01 = h01 + bf16r(bf16r(oa.y) + bhh);
        float r10 = h10 + bf16r(bf16r(ob.x) + bl), r11 = h11 + bf16r(bf16r(ob.y) + bhh);
        *reinterpret_cast<uint32_t*>(out + 2 * tid) = pack_bf16(r00, r01);
        *reinterpret_cast<uint32_t*>(out + 512 + 2 * tid) = pack_bf16(r10, r11);
    }
}

typedef CUresult (*PFN_encodeTiled)(CUtensorMap*, CUtensorMapDataType, cuuint32_t, void*, const cuuint64_t*,
                                    const cuuint64_t*, const cuuint32_t*, const cuuint32_t*, CUtensorMapInterleave,
                                    CUtensorMapSwizzle, CUtensorMapL2promotion, CUtensorMapFloatOOBfill);

}

extern "C" void kernel_launch(void* const* d_in, const int* in_sizes, int n_in, void* d_out, int out_size) {
    static PFN_encodeTiled enc = nullptr;
    if (!enc) {
        void* fn = nullptr;
        cudaDriverEntryPointQueryResult qres;
        cudaGetDriverEntryPoint("cuTensorMapEncodeTiled", &fn, cudaEnableDefault, &qres);
        enc = (PFN_encodeTiled)fn;
        cudaFuncSetAttribute(fused_kernel, cudaFuncAttributeMaxDynamicSharedMemorySize, SMEM_BYTES);
    }
    CUtensorMap mapK, mapV;
    cuuint64_t gdim[2] = {(cuuint64_t)DH, (cuuint64_t)NB * HKV * SK};
    cuuint64_t gstr[1] = {(cuuint64_t)DH * 2};
    cuuint32_t box[2] = {64, 16};
    cuuint32_t estr[2] = {1, 1};
    enc(&mapK, CU_TENSOR_MAP_DATA_TYPE_BFLOAT16, 2, d_in[1], gdim, gstr, box, estr, CU_TENSOR_MAP_INTERLEAVE_NONE,
        CU_TENSOR_MAP_SWIZZLE_128B, CU_TENSOR_MAP_L2_PROMOTION_L2_128B, CU_TENSOR_MAP_FLOAT_OOB_FILL_NONE);
    enc(&mapV, CU_TENSOR_MAP_DATA_TYPE_BFLOAT16, 2, d_in[2], gdim, gstr, box, estr, CU_TENSOR_MAP_INTERLEAVE_NONE,
        CU_TENSOR_MAP_SWIZZLE_128B, CU_TENSOR_MAP_L2_PROMOTION_L2_128B, CU_TENSOR_MAP_FLOAT_OOB_FILL_NONE);
    fused_kernel<<<NCTA, NTHREADS, SMEM_BYTES>>>(
        mapK, mapV, (const __nv_bfloat16*)d_in[0], (const __nv_bfloat16*)d_in[3], (const __nv_bfloat16*)d_in[4],
        (const __nv_bfloat16*)d_in[6], (const __nv_bfloat16*)d_in[7], (const __nv_bfloat16*)d_in[8],
        (const __nv_bfloat16*)d_in[9], (__nv_bfloat16*)d_out);
}
```

```cpp
#include <cuda_runtime.h>
#include <cuda_bf16.h>
#include <cuda.h>
#include <stdint.h>

namespace {

constexpr int NB = 2, DM = 512, HQ = 32, HKV = 8, SK = 8192, DH = 128, FF = 1792;
constexpr int NCTA = 128, NSPLIT = 8, KEYS_PER_CTA = SK / NSPLIT;
constexpr int NWARP = 8, NTHREADS = NWARP * 32;
constexpr int NSTAGE = 3;
constexpr int STAGE_BYTES = 8192;
constexpr int NBLK = KEYS_PER_CTA / (16 * NWARP);
constexpr int RING_BYTES = NWARP * NSTAGE * STAGE_BYTES;
constexpr int SMEM_BYTES = RING_BYTES + 4096 + 1024 + 1024;

__device__ __nv_bfloat16 g_q[NB * HQ * DH];
__device__ float g_pm[16 * NSPLIT * 4];
__device__ float g_pl[16 * NSPLIT * 4];
__device__ float g_po[16 * NSPLIT * 4 * DH];
__device__ float g_attn_acc[NB * DM];
__device__ float g_out_acc[4 * NB * DM];
__device__ unsigned g_bar;
__device__ unsigned g_done;

#define TS(i)
__device__ __forceinline__ uint32_t smem_u32(const void* p) {
    return (uint32_t)__cvta_generic_to_shared(p);
}
__device__ __forceinline__ float bf16r(float x) {
    return __bfloat162float(__float2bfloat16_rn(x));
}
__device__ __forceinline__ uint32_t pack_bf16(float lo, float hi) {
    __nv_bfloat162 v = __floats2bfloat162_rn(lo, hi);
    return *reinterpret_cast<uint32_t*>(&v);
}
__device__ __forceinline__ float bf_lo(uint32_t v) { return __uint_as_float(v << 16); }
__device__ __forceinline__ float bf_hi(uint32_t v) { return __uint_as_float(v & 0xffff0000u); }

__device__ __forceinline__ void mbar_init(uint32_t bar, uint32_t cnt) {
    asm volatile("mbarrier.init.shared::cta.b64 [%0], %1;" ::"r"(bar), "r"(cnt) : "memory");
}
__device__ __forceinline__ void mbar_expect_tx(uint32_t bar, uint32_t bytes) {
    asm volatile("mbarrier.arrive.expect_tx.shared::cta.b64 _, [%0], %1;" ::"r"(bar), "r"(bytes) : "memory");
}
__device__ __forceinline__ void mbar_wait(uint32_t bar, uint32_t parity) {
    asm volatile(
        "{\n"
        ".reg .pred p;\n"
        "WAIT_LOOP:\n"
        "mbarrier.try_wait.parity.shared::cta.b64 p, [%0], %1;\n"
        "@p bra WAIT_DONE;\n"
        "bra WAIT_LOOP;\n"
        "WAIT_DONE:\n"
        "}\n" ::"r"(bar), "r"(parity) : "memory");
}
__device__ __forceinline__ void tma_2d(uint32_t dst, const CUtensorMap* map, uint32_t bar, int c0, int c1) {
    asm volatile(
        "cp.async.bulk.tensor.2d.shared::cluster.global.mbarrier::complete_tx::bytes [%0], [%1, {%3, %4}], [%2];"
        ::"r"(dst), "l"(map), "r"(bar), "r"(c0), "r"(c1) : "memory");
}
__device__ __forceinline__ void ldsm_x4(uint32_t addr, uint32_t& r0, uint32_t& r1, uint32_t& r2, uint32_t& r3) {
    asm volatile("ldmatrix.sync.aligned.m8n8.x4.shared.b16 {%0,%1,%2,%3}, [%4];"
                 : "=r"(r0), "=r"(r1), "=r"(r2), "=r"(r3) : "r"(addr) : "memory");
}
__device__ __forceinline__ void ldsm_x4_t(uint32_t addr, uint32_t& r0, uint32_t& r1, uint32_t& r2, uint32_t& r3) {
    asm volatile("ldmatrix.sync.aligned.m8n8.x4.trans.shared.b16 {%0,%1,%2,%3}, [%4];"
                 : "=r"(r0), "=r"(r1), "=r"(r2), "=r"(r3) : "r"(addr) : "memory");
}
__device__ __forceinline__ void mma16816(float* c, uint32_t a0, uint32_t a1, uint32_t a2, uint32_t a3,
                                         uint32_t b0, uint32_t b1) {
    asm volatile(
        "mma.sync.aligned.m16n8k16.row.col.f32.bf16.bf16.f32 {%0,%1,%2,%3}, {%4,%5,%6,%7}, {%8,%9}, {%0,%1,%2,%3};"
        : "+f"(c[0]), "+f"(c[1]), "+f"(c[2]), "+f"(c[3])
        : "r"(a0), "r"(a1), "r"(a2), "r"(a3), "r"(b0), "r"(b1));
}
__device__ __forceinline__ unsigned ld_acquire(const unsigned* p) {
    unsigned v;
    asm volatile("ld.acquire.gpu.global.u32 %0, [%1];" : "=r"(v) : "l"(p) : "memory");
    return v;
}
__device__ __forceinline__ uint4 ldg_nc_v4(const void* p) {
    uint4 v;
    asm volatile("ld.global.nc.L1::no_allocate.v4.u32 {%0,%1,%2,%3}, [%4];"
                 : "=r"(v.x), "=r"(v.y), "=r"(v.z), "=r"(v.w) : "l"(p));
    return v;
}
__device__ __forceinline__ uint32_t ldg_nc_u32(const void* p) {
    uint32_t v;
    asm volatile("ld.global.nc.L1::no_allocate.u32 %0, [%1];" : "=r"(v) : "l"(p));
    return v;
}

__device__ __forceinline__ void red_v4(float* p, float a, float b, float c, float d) {
    asm volatile("red.global.add.v4.f32 [%0], {%1,%2,%3,%4};" ::"l"(p), "f"(a), "f"(b), "f"(c), "f"(d) : "memory");
}

__device__ __forceinline__ void grid_barrier() {
    __syncthreads();
    if (threadIdx.x == 0) {
        __threadfence();
        unsigned old = atomicAdd(&g_bar, 1u);
        unsigned target = (old / NCTA + 1u) * NCTA;
        unsigned iters = 0;
        while ((int)(ld_acquire(&g_bar) - target) < 0) {
            if (++iters > 20000000u) break;
        }
        __threadfence();
    }
    __syncthreads();
}

__device__ __forceinline__ void layernorm_2x512(float* v, float* red, int tid) {
    int warp = tid >> 5, lane = tid & 31;
    float a0 = v[2 * tid], a1 = v[2 * tid + 1], b0 = v[512 + 2 * tid], b1 = v[512 + 2 * tid + 1];
    float sa = a0 + a1, sb = b0 + b1;
#pragma unroll
    for (int o = 16; o > 0; o >>= 1) {
        sa += __shfl_xor_sync(0xffffffffu, sa, o);
        sb += __shfl_xor_sync(0xffffffffu, sb, o);
    }
    if (lane == 0) { red[warp] = sa; red[8 + warp] = sb; }
    __syncthreads();
    float ma = 0.f, mb = 0.f;
#pragma unroll
    for (int w = 0; w < 8; w++) { ma += red[w]; mb += red[8 + w]; }
    ma *= (1.f / 512.f); mb *= (1.f / 512.f);
    float da0 = a0 - ma, da1 = a1 - ma, db0 = b0 - mb, db1 = b1 - mb;
    float va = da0 * da0 + da1 * da1, vb = db0 * db0 + db1 * db1;
#pragma unroll
    for (int o = 16; o > 0; o >>= 1) {
        va += __shfl_xor_sync(0xffffffffu, va, o);
        vb += __shfl_xor_sync(0xffffffffu, vb, o);
    }
    __syncthreads();
    if (lane == 0) { red[16 + warp] = va; red[24 + warp] = vb; }
    __syncthreads();
    va = 0.f; vb = 0.f;
#pragma unroll
    for (int w = 0; w < 8; w++) { va += red[16 + w]; vb += red[24 + w]; }
    va = bf16r(va * (1.f / 512.f)); vb = bf16r(vb * (1.f / 512.f));
    float mra = bf16r(ma), mrb = bf16r(mb);
    float sda = bf16r(sqrtf(bf16r(va + 1e-5f))), sdb = bf16r(sqrtf(bf16r(vb + 1e-5f)));
    v[2 * tid] = bf16r(bf16r(a0 - mra) / sda);
    v[2 * tid + 1] = bf16r(bf16r(a1 - mra) / sda);
    v[512 + 2 * tid] = bf16r(bf16r(b0 - mrb) / sdb);
    v[512 + 2 * tid + 1] = bf16r(bf16r(b1 - mrb) / sdb);
    __syncthreads();
}

__device__ __forceinline__ float gelu_tanh(float x) {
    const float k0 = 0.7978845608028654f, k1 = 0.044715f;
    float inner = k0 * (x + k1 * x * x * x);
    return 0.5f * x * (1.f + tanhf(inner));
}

__global__ void __launch_bounds__(NTHREADS, 1)
fused_kernel(const __grid_constant__ CUtensorMap mapK, const __grid_constant__ CUtensorMap mapV,
             const __nv_bfloat16* __restrict__ x, const __nv_bfloat16* __restrict__ wq,
             const __nv_bfloat16* __restrict__ wo, const __nv_bfloat16* __restrict__ w1,
             const __nv_bfloat16* __restrict__ b1, const __nv_bfloat16* __restrict__ w2,
             const __nv_bfloat16* __restrict__ b2, __nv_bfloat16* __restrict__ out) {
    extern __shared__ __align__(1024) uint8_t smem_raw[];
    uint8_t* smem = smem_raw + ((1024u - (smem_u32(smem_raw) & 1023u)) & 1023u);
    uint8_t* ring = smem;
    uint64_t* bars = reinterpret_cast<uint64_t*>(smem + RING_BYTES);
    float* s_vec = reinterpret_cast<float*>(smem + RING_BYTES + 256);
    float* s_red = reinterpret_cast<float*>(smem + RING_BYTES + 256 + 4096);
    float* s_o = s_red + 64;
    float* s_f = s_o + 64;

    const int tid = threadIdx.x, warp = tid >> 5, lane = tid & 31;
    const int cta = blockIdx.x;
    const int bh = cta >> 3, split = cta & 7;
    const int b = bh >> 3, kvh = bh & 7;

    TS(0);
    const uint32_t ring_w = smem_u32(ring) + warp * (NSTAGE * STAGE_BYTES);
    const uint32_t bar_w = smem_u32(bars) + warp * (NSTAGE * 8);
    if (lane == 0) {
#pragma unroll
        for (int s = 0; s < NSTAGE; s++) mbar_init(bar_w + s * 8, 1);
        asm volatile("fence.mbarrier_init.release.cluster;" ::: "memory");
    }
    __syncwarp();

    uint32_t xv0 = ldg_nc_u32(x + 2 * tid);
    uint32_t xv1 = ldg_nc_u32(x + 512 + 2 * tid);
    uint4 wqv[8];
    {
        const __nv_bfloat16* p = wq + (size_t)(tid >> 2) * (HQ * DH) + cta * 32 + (tid & 3) * 8;
#pragma unroll
        for (int i = 0; i < 8; i++) wqv[i] = ldg_nc_v4(p + (size_t)i * 64 * (HQ * DH));
    }
    const int row0 = bh * SK + split * KEYS_PER_CTA + warp * 16;
    if (lane == 0) {
#pragma unroll
        for (int s = 0; s < NSTAGE; s++) {
            uint32_t dst = ring_w + s * STAGE_BYTES;
            uint32_t bar = bar_w + s * 8;
            int r = row0 + s * 128;
            mbar_expect_tx(bar, STAGE_BYTES);
            tma_2d(dst, &mapK, bar, 0, r);
            tma_2d(dst + 2048, &mapK, bar, 64, r);
            tma_2d(dst + 4096, &mapV, bar, 0, r);
            tma_2d(dst + 6144, &mapV, bar, 64, r);
        }
    }
    uint4 wov[8];
    uint4 w1v[4];
    uint4 w2v[4];
    const __nv_bfloat16* wo_p = wo + (size_t)((cta >> 2) * 128 + (tid >> 4)) * DM + (cta & 3) * 128 + (tid & 15) * 8;
    const int fcta = cta < 112 ? cta : 0;
    const __nv_bfloat16* w1_p = w1 + (size_t)(tid >> 1) * FF + fcta * 16 + (tid & 1) * 8;
    const __nv_bfloat16* w2_p = w2 + (size_t)(fcta * 16 + (tid >> 6)) * DM + (tid & 63) * 8;

    TS(1);
    s_vec[2 * tid] = bf_lo(xv0); s_vec[2 * tid + 1] = bf_hi(xv0);
    s_vec[512 + 2 * tid] = bf_lo(xv1); s_vec[512 + 2 * tid + 1] = bf_hi(xv1);
    __syncthreads();
    layernorm_2x512(s_vec, s_red, tid);

    {
        float acc[2][8];
#pragma unroll
        for (int i = 0; i < 8; i++) { acc[0][i] = 0.f; acc[1][i] = 0.f; }
#pragma unroll
        for (int i = 0; i < 8; i++) {
            int r = (tid >> 2) + i * 64;
            float x0 = s_vec[r], x1 = s_vec[512 + r];
            uint32_t w[4] = {wqv[i].x, wqv[i].y, wqv[i].z, wqv[i].w};
#pragma unroll
            for (int j = 0; j < 4; j++) {
                float lo = bf_lo(w[j]), hi = bf_hi(w[j]);
                acc[0][2 * j] += x0 * lo; acc[0][2 * j + 1] += x0 * hi;
                acc[1][2 * j] += x1 * lo; acc[1][2 * j + 1] += x1 * hi;
            }
        }
#pragma unroll
        for (int o = 4; o < 32; o <<= 1) {
#pragma unroll
            for (int i = 0; i < 8; i++) {
                acc[0][i] += __shfl_xor_sync(0xffffffffu, acc[0][i], o);
                acc[1][i] += __shfl_xor_sync(0xffffffffu, acc[1][i], o);
            }
        }
        __shared__ float s_qpart[NWARP][2][32];
        if (lane < 4) {
#pragma unroll
            for (int i = 0; i < 8; i++) {
                s_qpart[warp][0][lane * 8 + i] = acc[0][i];
                s_qpart[warp][1][lane * 8 + i] = acc[1][i];
            }
        }
        __syncthreads();
        if (tid < 64) {
            int bb = tid >> 5, c = tid & 31;
            float s = 0.f;
#pragma unroll
            for (int w = 0; w < NWARP; w++) s += s_qpart[w][bb][c];
            g_q[bb * (HQ * DH) + cta * 32 + c] = __float2bfloat16_rn(s);
        }
        if (cta == 0) {
            for (int i = tid; i < NB * DM; i += NTHREADS) g_attn_acc[i] = 0.f;
            for (int i = tid; i < 4 * NB * DM; i += NTHREADS) g_out_acc[i] = 0.f;
        }
    }
    TS(2);
    grid_barrier();
    TS(3);

    uint32_t qa[8][2];
    {
        int hl = lane >> 2;
        const __nv_bfloat16* qp = g_q + b * (HQ * DH) + (kvh * 4 + (hl & 3)) * DH + (lane & 3) * 2;
#pragma unroll
        for (int ks = 0; ks < 8; ks++) {
            uint32_t v0 = __ldcg(reinterpret_cast<const unsigned*>(qp + ks * 16));
            uint32_t v1 = __ldcg(reinterpret_cast<const unsigned*>(qp + ks * 16 + 8));
            qa[ks][0] = hl < 4 ? v0 : 0u;
            qa[ks][1] = hl < 4 ? v1 : 0u;
        }
    }

    float oacc[16][4];
#pragma unroll
    for (int j = 0; j < 16; j++) { oacc[j][0] = 0.f; oacc[j][1] = 0.f; oacc[j][2] = 0.f; oacc[j][3] = 0.f; }
    float m_run = -INFINITY, l_run = 0.f;
    const float scale = 0.08838834764831845f;
    const float LOG2E = 1.4426950408889634f;

    const int lrow = lane & 7, lmat = lane >> 3;
    const int k_row = (lmat >> 1) * 8 + lrow;
    const int k_cofs = lmat & 1;
    const int v_row = (lmat & 1) * 8 + lrow;
    const int v_cofs = lmat >> 1;

#pragma unroll
    for (int it = 0; it < NBLK; it++) {
        wov[it] = ldg_nc_v4(wo_p + (size_t)it * 16 * DM);
        if (it < 4) w1v[it] = ldg_nc_v4(w1_p + (size_t)it * 128 * FF);
        else w2v[it - 4] = ldg_nc_v4(w2_p + (size_t)(it - 4) * 4 * DM);
        const int s = it % NSTAGE;
        const uint32_t parity = (it / NSTAGE) & 1;
        const uint32_t st = ring_w + s * STAGE_BYTES;
        mbar_wait(bar_w + s * 8, parity);

        float sc[2][4];
#pragma unroll
        for (int j = 0; j < 2; j++) { sc[j][0] = 0.f; sc[j][1] = 0.f; sc[j][2] = 0.f; sc[j][3] = 0.f; }
#pragma unroll
        for (int ks = 0; ks < 8; ks++) {
            int chunk = (ks & 3) * 2 + k_cofs;
            uint32_t addr = st + (ks >> 2) * 2048 + k_row * 128 + ((chunk ^ (k_row & 7)) << 4);
            uint32_t r0, r1, r2, r3;
            ldsm_x4(addr, r0, r1, r2, r3);
            mma16816(sc[0], qa[ks][0], 0u, qa[ks][1], 0u, r0, r1);
            mma16816(sc[1], qa[ks][0], 0u, qa[ks][1], 0u, r2, r3);
        }
        float v00 = bf16r(bf16r(sc[0][0]) * scale), v01 = bf16r(bf16r(sc[0][1]) * scale);
        float v10 = bf16r(bf16r(sc[1][0]) * scale), v11 = bf16r(bf16r(sc[1][1]) * scale);
        float mx = fmaxf(fmaxf(v00, v01), fmaxf(v10, v11));
        mx = fmaxf(mx, __shfl_xor_sync(0xffffffffu, mx, 1));
        mx = fmaxf(mx, __shfl_xor_sync(0xffffffffu, mx, 2));
        float m_new = fmaxf(m_run, mx);
        float corr = exp2f((m_run - m_new) * LOG2E);
        float p00 = exp2f((v00 - m_new) * LOG2E), p01 = exp2f((v01 - m_new) * LOG2E);
        float p10 = exp2f((v10 - m_new) * LOG2E), p11 = exp2f((v11 - m_new) * LOG2E);
        l_run = l_run * corr + (p00 + p01 + p10 + p11);
        m_run = m_new;
        uint32_t pa0 = pack_bf16(p00, p01), pa2 = pack_bf16(p10, p11);
#pragma unroll
        for (int j = 0; j < 16; j++) { oacc[j][0] *= corr; oacc[j][1] *= corr; }
#pragma unroll
        for (int jj = 0; jj < 8; jj++) {
            int chunk = (jj & 3) * 2 + v_cofs;
            uint32_t addr = st + 4096 + (jj >> 2) * 2048 + v_row * 128 + ((chunk ^ (v_row & 7)) << 4);
            uint32_t r0, r1, r2, r3;
            ldsm_x4_t(addr, r0, r1, r2, r3);
            mma16816(oacc[2 * jj], pa0, 0u, pa2, 0u, r0, r1);
            mma16816(oacc[2 * jj + 1], pa0, 0u, pa2, 0u, r2, r3);
        }
        __syncwarp();
        if (lane == 0 && it + NSTAGE < NBLK) {
            uint32_t bar = bar_w + s * 8;
            int r = row0 + (it + NSTAGE) * 128;
            mbar_expect_tx(bar, STAGE_BYTES);
            tma_2d(st, &mapK, bar, 0, r);
            tma_2d(st + 2048, &mapK, bar, 64, r);
            tma_2d(st + 4096, &mapV, bar, 0, r);
            tma_2d(st + 6144, &mapV, bar, 64, r);
        }
    }
    TS(4);
    l_run += __shfl_xor_sync(0xffffffffu, l_run, 1);
    l_run += __shfl_xor_sync(0xffffffffu, l_run, 2);

    __syncthreads();
    float* r_o = reinterpret_cast<float*>(ring);
    float* r_m = reinterpret_cast<float*>(ring + 16384);
    float* r_l = r_m + 32;
    if (lane < 16) {
        int hl = lane >> 2;
#pragma unroll
        for (int j = 0; j < 16; j++) {
            float2 v = make_float2(oacc[j][0], oacc[j][1]);
            *reinterpret_cast<float2*>(&r_o[(warp * 4 + hl) * DH + j * 8 + (lane & 3) * 2]) = v;
        }
        if ((lane & 3) == 0) { r_m[warp * 4 + hl] = m_run; r_l[warp * 4 + hl] = l_run; }
    }
    __syncthreads();
    {
        int hl = tid >> 6, d = (tid & 63) * 2;
        float mm = -INFINITY;
#pragma unroll
        for (int w = 0; w < NWARP; w++) mm = fmaxf(mm, r_m[w * 4 + hl]);
        float o0 = 0.f, o1 = 0.f, ll = 0.f;
#pragma unroll
        for (int w = 0; w < NWARP; w++) {
            float c = exp2f((r_m[w * 4 + hl] - mm) * LOG2E);
            float2 v = *reinterpret_cast<float2*>(&r_o[(w * 4 + hl) * DH + d]);
            o0 += c * v.x; o1 += c * v.y; ll += c * r_l[w * 4 + hl];
        }
        int pidx = (cta * 4 + hl);
        *reinterpret_cast<float2*>(&g_po[(size_t)pidx * DH + d]) = make_float2(o0, o1);
        if ((tid & 63) == 0) { g_pm[pidx] = mm; g_pl[pidx] = ll; }
    }
    TS(5);
    grid_barrier();
    TS(6);

    {
        int head = cta >> 2;
        int kv = head >> 2, hl = head & 3;
        {
            int bb = tid >> 7, d = tid & 127;
            int base = ((bb * 8 + kv) * NSPLIT) * 4 + hl;
            float pm[NSPLIT], pl[NSPLIT], po[NSPLIT];
#pragma unroll
            for (int s = 0; s < NSPLIT; s++) {
                pm[s] = __ldcg(&g_pm[base + s * 4]);
                pl[s] = __ldcg(&g_pl[base + s * 4]);
                po[s] = __ldcg(&g_po[(size_t)(base + s * 4) * DH + d]);
            }
            float mm = -INFINITY;
#pragma unroll
            for (int s = 0; s < NSPLIT; s++) mm = fmaxf(mm, pm[s]);
            float oo = 0.f, ll = 0.f;
#pragma unroll
            for (int s = 0; s < NSPLIT; s++) {
                float c = exp2f((pm[s] - mm) * LOG2E);
                oo += c * po[s]; ll += c * pl[s];
            }
            s_vec[tid] = bf16r(oo / ll);
        }
        __syncthreads();
        float a[2][8];
#pragma unroll
        for (int j = 0; j < 8; j++) { a[0][j] = 0.f; a[1][j] = 0.f; }
#pragma unroll
        for (int i = 0; i < 8; i++) {
            int r = (tid >> 4) + 16 * i;
            float o0 = s_vec[r], o1 = s_vec[128 + r];
            uint32_t w[4] = {wov[i].x, wov[i].y, wov[i].z, wov[i].w};
#pragma unroll
            for (int j = 0; j < 4; j++) {
                float lo = bf_lo(w[j]), hi = bf_hi(w[j]);
                a[0][2 * j] += o0 * lo; a[0][2 * j + 1] += o0 * hi;
                a[1][2 * j] += o1 * lo; a[1][2 * j + 1] += o1 * hi;
            }
        }
#pragma unroll
        for (int j = 0; j < 8; j++) {
            a[0][j] += __shfl_xor_sync(0xffffffffu, a[0][j], 16);
            a[1][j] += __shfl_xor_sync(0xffffffffu, a[1][j], 16);
        }
        float* s_p = reinterpret_cast<float*>(ring);
        if (lane < 16) {
#pragma unroll
            for (int bb = 0; bb < 2; bb++) {
                float4* dst = reinterpret_cast<float4*>(&s_p[(warp * 2 + bb) * 128 + lane * 8]);
                dst[0] = make_float4(a[bb][0], a[bb][1], a[bb][2], a[bb][3]);
                dst[1] = make_float4(a[bb][4], a[bb][5], a[bb][6], a[bb][7]);
            }
        }
        __syncthreads();
        if (tid < 64) {
            int bb = tid >> 5, c4 = (tid & 31) * 4;
            float4 acc = make_float4(0.f, 0.f, 0.f, 0.f);
#pragma unroll
            for (int w = 0; w < NWARP; w++) {
                float4 v = *reinterpret_cast<float4*>(&s_p[(w * 2 + bb) * 128 + c4]);
                acc.x += v.x; acc.y += v.y; acc.z += v.z; acc.w += v.w;
            }
            red_v4(&g_attn_acc[bb * 512 + (cta & 3) * 128 + c4], acc.x, acc.y, acc.z, acc.w);
        }
    }
    TS(7);
    grid_barrier();
    TS(8);

    float h00, h01, h10, h11;
    {
        float2 aa = __ldcg(reinterpret_cast<const float2*>(&g_attn_acc[2 * tid]));
        float2 ab = __ldcg(reinterpret_cast<const float2*>(&g_attn_acc[512 + 2 * tid]));
        h00 = bf16r(bf_lo(xv0) + bf16r(aa.x)); h01 = bf16r(bf_hi(xv0) + bf16r(aa.y));
        h10 = bf16r(bf_lo(xv1) + bf16r(ab.x)); h11 = bf16r(bf_hi(xv1) + bf16r(ab.y));
        s_vec[2 * tid] = h00; s_vec[2 * tid + 1] = h01;
        s_vec[512 + 2 * tid] = h10; s_vec[512 + 2 * tid + 1] = h11;
        __syncthreads();
        layernorm_2x512(s_vec, s_red, tid);
        if (cta < 112) {
            float f[2][8];
#pragma unroll
            for (int j = 0; j < 8; j++) { f[0][j] = 0.f; f[1][j] = 0.f; }
#pragma unroll
            for (int i = 0; i < 4; i++) {
                int r = (tid >> 1) + 128 * i;
                float n0 = s_vec[r], n1 = s_vec[512 + r];
                uint32_t w[4] = {w1v[i].x, w1v[i].y, w1v[i].z, w1v[i].w};
#pragma unroll
                for (int j = 0; j < 4; j++) {
                    float lo = bf_lo(w[j]), hi = bf_hi(w[j]);
                    f[0][2 * j] += n0 * lo; f[0][2 * j + 1] += n0 * hi;
                    f[1][2 * j] += n1 * lo; f[1][2 * j + 1] += n1 * hi;
                }
            }
#pragma unroll
            for (int o = 2; o < 32; o <<= 1) {
#pragma unroll
                for (int j = 0; j < 8; j++) {
                    f[0][j] += __shfl_xor_sync(0xffffffffu, f[0][j], o);
                    f[1][j] += __shfl_xor_sync(0xffffffffu, f[1][j], o);
                }
            }
            float* s_fp = reinterpret_cast<float*>(ring);
            if (lane < 2) {
#pragma unroll
                for (int j = 0; j < 8; j++) {
                    s_fp[(warp * 2 + 0) * 16 + lane * 8 + j] = f[0][j];
                    s_fp[(warp * 2 + 1) * 16 + lane * 8 + j] = f[1][j];
                }
            }
            __syncthreads();
            if (tid < 32) {
                int bb = tid >> 4, c = tid & 15;
                float sacc = 0.f;
#pragma unroll
                for (int w = 0; w < NWARP; w++) sacc += s_fp[(w * 2 + bb) * 16 + c];
                float bias = __bfloat162float(b1[cta * 16 + c]);
                float hh = bf16r(bf16r(sacc) + bias);
                s_f[tid] = bf16r(gelu_tanh(hh));
            }
            __syncthreads();
            float a[2][8];
#pragma unroll
            for (int j = 0; j < 8; j++) { a[0][j] = 0.f; a[1][j] = 0.f; }
#pragma unroll
            for (int i = 0; i < 4; i++) {
                int r = (tid >> 6) + 4 * i;
                float f0 = s_f[r], f1 = s_f[16 + r];
                uint32_t w[4] = {w2v[i].x, w2v[i].y, w2v[i].z, w2v[i].w};
#pragma unroll
                for (int j = 0; j < 4; j++) {
                    float lo = bf_lo(w[j]), hi = bf_hi(w[j]);
                    a[0][2 * j] += f0 * lo; a[0][2 * j + 1] += f0 * hi;
                    a[1][2 * j] += f1 * lo; a[1][2 * j + 1] += f1 * hi;
                }
            }
            float* s_p = reinterpret_cast<float*>(ring) + 1024;
            {
                int g = tid >> 6, c8 = (tid & 63) * 8;
#pragma unroll
                for (int bb = 0; bb < 2; bb++) {
                    float4* dst = reinterpret_cast<float4*>(&s_p[(g * 2 + bb) * 512 + c8]);
                    dst[0] = make_float4(a[bb][0], a[bb][1], a[bb][2], a[bb][3]);
                    dst[1] = make_float4(a[bb][4], a[bb][5], a[bb][6], a[bb][7]);
                }
            }
            __syncthreads();
            {
                int bb = tid >> 7, c4 = (tid & 127) * 4;
                float4 acc = make_float4(0.f, 0.f, 0.f, 0.f);
#pragma unroll
                for (int g = 0; g < 4; g++) {
                    float4 v = *reinterpret_cast<float4*>(&s_p[(g * 2 + bb) * 512 + c4]);
                    acc.x += v.x; acc.y += v.y; acc.z += v.z; acc.w += v.w;
                }
                red_v4(&g_out_acc[(cta & 3) * 1024 + bb * 512 + c4], acc.x, acc.y, acc.z, acc.w);
            }
        }
    }
    TS(9);
    __shared__ unsigned s_last;
    __syncthreads();
    if (tid == 0) {
        __threadfence();
        unsigned old = atomicAdd(&g_done, 1u);
        s_last = ((old % NCTA) == NCTA - 1) ? 1u : 0u;
        __threadfence();
    }
    __syncthreads();
    if (s_last) {
        float2 oa = make_float2(0.f, 0.f), ob = make_float2(0.f, 0.f);
#pragma unroll
        for (int c = 0; c < 4; c++) {
            float2 va = __ldcg(reinterpret_cast<const float2*>(&g_out_acc[c * 1024 + 2 * tid]));
            float2 vb = __ldcg(reinterpret_cast<const float2*>(&g_out_acc[c * 1024 + 512 + 2 * tid]));
            oa.x += va.x; oa.y += va.y; ob.x += vb.x; ob.y += vb.y;
        }
        uint32_t bb = *reinterpret_cast<const uint32_t*>(b2 + 2 * tid);
        float bl = bf_lo(bb), bhh = bf_hi(bb);
        float r00 = h00 + bf16r(bf16r(oa.x) + bl), r01 = h01 + bf16r(bf16r(oa.y) + bhh);
        float r10 = h10 + bf16r(bf16r(ob.x) + bl), r11 = h11 + bf16r(bf16r(ob.y) + bhh);
        *reinterpret_cast<uint32_t*>(out + 2 * tid) = pack_bf16(r00, r01);
        *reinterpret_cast<uint32_t*>(out + 512 + 2 * tid) = pack_bf16(r10, r11);
    }
    TS(10);
}

typedef CUresult (*PFN_encodeTiled)(CUtensorMap*, CUtensorMapDataType, cuuint32_t, void*, const cuuint64_t*,
                                    const cuuint64_t*, const cuuint32_t*, const cuuint32_t*, CUtensorMapInterleave,
                                    CUtensorMapSwizzle, CUtensorMapL2promotion, CUtensorMapFloatOOBfill);

}

extern "C" void kernel_launch(void* const* d_in, const int* in_sizes, int n_in, void* d_out, int out_size) {
    static PFN_encodeTiled enc = nullptr;
    if (!enc) {
        void* fn = nullptr;
        cudaDriverEntryPointQueryResult qres;
        cudaGetDriverEntryPoint("cuTensorMapEncodeTiled", &fn, cudaEnableDefault, &qres);
        enc = (PFN_encodeTiled)fn;
        cudaFuncSetAttribute(fused_kernel, cudaFuncAttributeMaxDynamicSharedMemorySize, SMEM_BYTES);
    }
    CUtensorMap mapK, mapV;
    cuuint64_t gdim[2] = {(cuuint64_t)DH, (cuuint64_t)NB * HKV * SK};
    cuuint64_t gstr[1] = {(cuuint64_t)DH * 2};
    cuuint32_t box[2] = {64, 16};
    cuuint32_t estr[2] = {1, 1};
    enc(&mapK, CU_TENSOR_MAP_DATA_TYPE_BFLOAT16, 2, d_in[1], gdim, gstr, box, estr, CU_TENSOR_MAP_INTERLEAVE_NONE,
        CU_TENSOR_MAP_SWIZZLE_128B, CU_TENSOR_MAP_L2_PROMOTION_L2_128B, CU_TENSOR_MAP_FLOAT_OOB_FILL_NONE);
    enc(&mapV, CU_TENSOR_MAP_DATA_TYPE_BFLOAT16, 2, d_in[2], gdim, gstr, box, estr, CU_TENSOR_MAP_INTERLEAVE_NONE,
        CU_TENSOR_MAP_SWIZZLE_128B, CU_TENSOR_MAP_L2_PROMOTION_L2_128B, CU_TENSOR_MAP_FLOAT_OOB_FILL_NONE);
    fused_kernel<<<NCTA, NTHREADS, SMEM_BYTES>>>(
        mapK, mapV, (const __nv_bfloat16*)d_in[0], (const __nv_bfloat16*)d_in[3], (const __nv_bfloat16*)d_in[4],
        (const __nv_bfloat16*)d_in[6], (const __nv_bfloat16*)d_in[7], (const __nv_bfloat16*)d_in[8],
        (const __nv_bfloat16*)d_in[9], (__nv_bfloat16*)d_out);
}
```

```cpp
#include <cuda_runtime.h>
#include <cuda_bf16.h>
#include <cuda.h>
#include <stdint.h>

namespace {

constexpr int NB = 2, DM = 512, HQ = 32, HKV = 8, SK = 8192, DH = 128, FF = 1792;
constexpr int NCTA = 128, NSPLIT = 8, KEYS_PER_CTA = SK / NSPLIT;
constexpr int NWARP = 8, NTHREADS = NWARP * 32;
constexpr int NSTAGE = 3;
#define REST_MODE 1
#define EARLY_W 1
#define QTRIES (1 << 20)
#define L2PF 0
#define LATE_W 0
#define PF_IT 1
#define PRE_STAGES 1
constexpr int STAGE_BYTES = 8192;
constexpr int NBLK = KEYS_PER_CTA / (16 * NWARP);
constexpr int RING_BYTES = NWARP * NSTAGE * STAGE_BYTES;
constexpr int SMEM_BYTES = RING_BYTES + 4096 + 2048 + 1024;

__device__ unsigned long long g_q64[NB * HQ * DH / 2];
__device__ unsigned g_epoch;
__device__ float g_pm[16 * NSPLIT * 4];
__device__ float g_pl[16 * NSPLIT * 4];
__device__ float g_po[16 * NSPLIT * 4 * DH];
__device__ float g_attn_acc[NB * DM];
__device__ float g_out_acc[4 * NB * DM];
__device__ unsigned g_bar;
__device__ unsigned g_done;

#define TS(i)
#define CTA_SYNC() asm volatile("bar.sync 1, 256;" ::: "memory")
__device__ __forceinline__ uint32_t smem_u32(const void* p) {
    return (uint32_t)__cvta_generic_to_shared(p);
}
__device__ __forceinline__ float bf16r(float x) {
    return __bfloat162float(__float2bfloat16_rn(x));
}
__device__ __forceinline__ uint32_t pack_bf16(float lo, float hi) {
    __nv_bfloat162 v = __floats2bfloat162_rn(lo, hi);
    return *reinterpret_cast<uint32_t*>(&v);
}
__device__ __forceinline__ float bf_lo(uint32_t v) { return __uint_as_float(v << 16); }
__device__ __forceinline__ float bf_hi(uint32_t v) { return __uint_as_float(v & 0xffff0000u); }

__device__ __forceinline__ void mbar_init(uint32_t bar, uint32_t cnt) {
    asm volatile("mbarrier.init.shared::cta.b64 [%0], %1;" ::"r"(bar), "r"(cnt) : "memory");
}
__device__ __forceinline__ void mbar_expect_tx(uint32_t bar, uint32_t bytes) {
    asm volatile("mbarrier.arrive.expect_tx.shared::cta.b64 _, [%0], %1;" ::"r"(bar), "r"(bytes) : "memory");
}
__device__ __forceinline__ void mbar_wait(uint32_t bar, uint32_t parity) {
    for (int i = 0; i < (1 << 22); i++) {
        uint32_t ok;
        asm volatile(
            "{\n"
            ".reg .pred p;\n"
            "mbarrier.try_wait.parity.shared::cta.b64 p, [%1], %2;\n"
            "selp.u32 %0, 1, 0, p;\n"
            "}\n" : "=r"(ok) : "r"(bar), "r"(parity) : "memory");
        if (ok) break;
    }
}
__device__ __forceinline__ void tma_2d(uint32_t dst, const CUtensorMap* map, uint32_t bar, int c0, int c1) {
    asm volatile(
        "cp.async.bulk.tensor.2d.shared::cluster.global.mbarrier::complete_tx::bytes [%0], [%1, {%3, %4}], [%2];"
        ::"r"(dst), "l"(map), "r"(bar), "r"(c0), "r"(c1) : "memory");
}
__device__ __forceinline__ void ldsm_x4(uint32_t addr, uint32_t& r0, uint32_t& r1, uint32_t& r2, uint32_t& r3) {
    asm volatile("ldmatrix.sync.aligned.m8n8.x4.shared.b16 {%0,%1,%2,%3}, [%4];"
                 : "=r"(r0), "=r"(r1), "=r"(r2), "=r"(r3) : "r"(addr) : "memory");
}
__device__ __forceinline__ void ldsm_x4_t(uint32_t addr, uint32_t& r0, uint32_t& r1, uint32_t& r2, uint32_t& r3) {
    asm volatile("ldmatrix.sync.aligned.m8n8.x4.trans.shared.b16 {%0,%1,%2,%3}, [%4];"
                 : "=r"(r0), "=r"(r1), "=r"(r2), "=r"(r3) : "r"(addr) : "memory");
}
__device__ __forceinline__ void mma16816(float* c, uint32_t a0, uint32_t a1, uint32_t a2, uint32_t a3,
                                         uint32_t b0, uint32_t b1) {
    asm volatile(
        "mma.sync.aligned.m16n8k16.row.col.f32.bf16.bf16.f32 {%0,%1,%2,%3}, {%4,%5,%6,%7}, {%8,%9}, {%0,%1,%2,%3};"
        : "+f"(c[0]), "+f"(c[1]), "+f"(c[2]), "+f"(c[3])
        : "r"(a0), "r"(a1), "r"(a2), "r"(a3), "r"(b0), "r"(b1));
}
__device__ __forceinline__ unsigned ld_acquire(const unsigned* p) {
    unsigned v;
    asm volatile("ld.acquire.gpu.global.u32 %0, [%1];" : "=r"(v) : "l"(p) : "memory");
    return v;
}
__device__ __forceinline__ uint4 ldg_nc_v4(const void* p) {
    uint4 v;
    asm volatile("ld.global.nc.L1::no_allocate.v4.u32 {%0,%1,%2,%3}, [%4];"
                 : "=r"(v.x), "=r"(v.y), "=r"(v.z), "=r"(v.w) : "l"(p));
    return v;
}
__device__ __forceinline__ uint32_t ldg_nc_u32(const void* p) {
    uint32_t v;
    asm volatile("ld.global.nc.L1::no_allocate.u32 %0, [%1];" : "=r"(v) : "l"(p));
    return v;
}

__device__ __forceinline__ void red_v4(float* p, float a, float b, float c, float d) {
    asm volatile("red.global.add.v4.f32 [%0], {%1,%2,%3,%4};" ::"l"(p), "f"(a), "f"(b), "f"(c), "f"(d) : "memory");
}

__device__ __forceinline__ void grid_barrier() {
    CTA_SYNC();
    if (threadIdx.x == 0) {
        __threadfence();
        unsigned old = atomicAdd(&g_bar, 1u);
        unsigned target = (old / NCTA + 1u) * NCTA;
        unsigned iters = 0;
        while ((int)(ld_acquire(&g_bar) - target) < 0) {
            if (++iters > 2000000u) break;
        }
        __threadfence();
    }
    CTA_SYNC();
}

__device__ __forceinline__ void layernorm_2x512(float* v, float* red, int tid) {
    int warp = tid >> 5, lane = tid & 31;
    float a0 = v[2 * tid], a1 = v[2 * tid + 1], b0 = v[512 + 2 * tid], b1 = v[512 + 2 * tid + 1];
    float sa = a0 + a1, sb = b0 + b1;
#pragma unroll
    for (int o = 16; o > 0; o >>= 1) {
        sa += __shfl_xor_sync(0xffffffffu, sa, o);
        sb += __shfl_xor_sync(0xffffffffu, sb, o);
    }
    if (lane == 0) { red[warp] = sa; red[8 + warp] = sb; }
    CTA_SYNC();
    float ma = 0.f, mb = 0.f;
#pragma unroll
    for (int w = 0; w < 8; w++) { ma += red[w]; mb += red[8 + w]; }
    ma *= (1.f / 512.f); mb *= (1.f / 512.f);
    float da0 = a0 - ma, da1 = a1 - ma, db0 = b0 - mb, db1 = b1 - mb;
    float va = da0 * da0 + da1 * da1, vb = db0 * db0 + db1 * db1;
#pragma unroll
    for (int o = 16; o > 0; o >>= 1) {
        va += __shfl_xor_sync(0xffffffffu, va, o);
        vb += __shfl_xor_sync(0xffffffffu, vb, o);
    }
    CTA_SYNC();
    if (lane == 0) { red[16 + warp] = va; red[24 + warp] = vb; }
    CTA_SYNC();
    va = 0.f; vb = 0.f;
#pragma unroll
    for (int w = 0; w < 8; w++) { va += red[16 + w]; vb += red[24 + w]; }
    va = bf16r(va * (1.f / 512.f)); vb = bf16r(vb * (1.f / 512.f));
    float mra = bf16r(ma), mrb = bf16r(mb);
    float sda = bf16r(sqrtf(bf16r(va + 1e-5f))), sdb = bf16r(sqrtf(bf16r(vb + 1e-5f)));
    v[2 * tid] = bf16r(bf16r(a0 - mra) / sda);
    v[2 * tid + 1] = bf16r(bf16r(a1 - mra) / sda);
    v[512 + 2 * tid] = bf16r(bf16r(b0 - mrb) / sdb);
    v[512 + 2 * tid + 1] = bf16r(bf16r(b1 - mrb) / sdb);
    CTA_SYNC();
}

__device__ __forceinline__ float gelu_tanh(float x) {
    const float k0 = 0.7978845608028654f, k1 = 0.044715f;
    float inner = k0 * (x + k1 * x * x * x);
    return 0.5f * x * (1.f + tanhf(inner));
}

__global__ void __launch_bounds__(NTHREADS, 1)
fused_kernel(const __grid_constant__ CUtensorMap mapK, const __grid_constant__ CUtensorMap mapV,
             const __nv_bfloat16* __restrict__ x, const __nv_bfloat16* __restrict__ wq,
             const __nv_bfloat16* __restrict__ wo, const __nv_bfloat16* __restrict__ w1,
             const __nv_bfloat16* __restrict__ b1, const __nv_bfloat16* __restrict__ w2,
             const __nv_bfloat16* __restrict__ b2, __nv_bfloat16* __restrict__ out) {
    extern __shared__ __align__(1024) uint8_t smem_raw[];
    uint8_t* smem = smem_raw + ((1024u - (smem_u32(smem_raw) & 1023u)) & 1023u);
    uint8_t* ring = smem;
    uint64_t* bars = reinterpret_cast<uint64_t*>(smem + RING_BYTES);
    float* s_vec = reinterpret_cast<float*>(smem + RING_BYTES + 256);
    float* s_red = reinterpret_cast<float*>(smem + RING_BYTES + 256 + 4096);
    float* s_o = s_red + 64;
    float* s_f = s_o + 64;

    const int tid = threadIdx.x, warp = tid >> 5, lane = tid & 31;
    const int cta = blockIdx.x;
    const int bh = cta >> 3, split = cta & 7;
    const int b = bh >> 3, kvh = bh & 7;

    TS(0);
    const uint32_t ring_w = smem_u32(ring) + warp * (NSTAGE * STAGE_BYTES);
    const uint32_t bar_w = smem_u32(bars) + warp * (NSTAGE * 8);
    if (lane == 0) {
#pragma unroll
        for (int s = 0; s < NSTAGE; s++) mbar_init(bar_w + s * 8, 1);
        asm volatile("fence.mbarrier_init.release.cluster;" ::: "memory");
    }
    __syncwarp();
    const unsigned epoch = __ldcg(&g_epoch) + 1u;
    uint32_t xv0 = ldg_nc_u32(x + 2 * tid);
    uint32_t xv1 = ldg_nc_u32(x + 512 + 2 * tid);
    uint4 wqv[8];
    {
        const __nv_bfloat16* p = wq + (size_t)(tid >> 2) * (HQ * DH) + cta * 32 + (tid & 3) * 8;
#pragma unroll
        for (int i = 0; i < 8; i++) wqv[i] = ldg_nc_v4(p + (size_t)i * 64 * (HQ * DH));
    }
    const int row0 = bh * SK + split * KEYS_PER_CTA + warp * 16;
    auto issue_stage = [&](int blk) {
        const int s = blk % NSTAGE;
        uint32_t dst = ring_w + s * STAGE_BYTES;
        uint32_t bar = bar_w + s * 8;
        int r = row0 + blk * 128;
        mbar_expect_tx(bar, STAGE_BYTES);
        tma_2d(dst, &mapK, bar, 0, r);
        tma_2d(dst + 2048, &mapK, bar, 64, r);
        tma_2d(dst + 4096, &mapV, bar, 0, r);
        tma_2d(dst + 6144, &mapV, bar, 64, r);
    };
    if (lane == 0) {
#pragma unroll
        for (int s = 0; s < NSTAGE; s++) issue_stage(s);
    }
    uint4 wov[8];
    uint4 w1v[4];
    uint4 w2v[4];
    const __nv_bfloat16* wo_p = wo + (size_t)((cta >> 2) * 128 + (tid >> 4)) * DM + (cta & 3) * 128 + (tid & 15) * 8;
    const int fcta = cta < 112 ? cta : 0;
    const __nv_bfloat16* w1_p = w1 + (size_t)(tid >> 1) * FF + fcta * 16 + (tid & 1) * 8;
    const __nv_bfloat16* w2_p = w2 + (size_t)(fcta * 16 + (tid >> 6)) * DM + (tid & 63) * 8;
#pragma unroll
    for (int it = 0; it < 8; it++) {
        wov[it] = ldg_nc_v4(wo_p + (size_t)it * 16 * DM);
        if (it < 4) w1v[it] = ldg_nc_v4(w1_p + (size_t)it * 128 * FF);
        else w2v[it - 4] = ldg_nc_v4(w2_p + (size_t)(it - 4) * 4 * DM);
    }

    TS(1);
    s_vec[2 * tid] = bf_lo(xv0); s_vec[2 * tid + 1] = bf_hi(xv0);
    s_vec[512 + 2 * tid] = bf_lo(xv1); s_vec[512 + 2 * tid + 1] = bf_hi(xv1);
    CTA_SYNC();
    layernorm_2x512(s_vec, s_red, tid);

    {
        float acc[2][8];
#pragma unroll
        for (int i = 0; i < 8; i++) { acc[0][i] = 0.f; acc[1][i] = 0.f; }
#pragma unroll
        for (int i = 0; i < 8; i++) {
            int r = (tid >> 2) + i * 64;
            float x0 = s_vec[r], x1 = s_vec[512 + r];
            uint32_t w[4] = {wqv[i].x, wqv[i].y, wqv[i].z, wqv[i].w};
#pragma unroll
            for (int j = 0; j < 4; j++) {
                float lo = bf_lo(w[j]), hi = bf_hi(w[j]);
                acc[0][2 * j] += x0 * lo; acc[0][2 * j + 1] += x0 * hi;
                acc[1][2 * j] += x1 * lo; acc[1][2 * j + 1] += x1 * hi;
            }
        }
#pragma unroll
        for (int o = 4; o < 32; o <<= 1) {
#pragma unroll
            for (int i = 0; i < 8; i++) {
                acc[0][i] += __shfl_xor_sync(0xffffffffu, acc[0][i], o);
                acc[1][i] += __shfl_xor_sync(0xffffffffu, acc[1][i], o);
            }
        }
        __shared__ float s_qpart[NWARP][2][32];
        if (lane < 4) {
#pragma unroll
            for (int i = 0; i < 8; i++) {
                s_qpart[warp][0][lane * 8 + i] = acc[0][i];
                s_qpart[warp][1][lane * 8 + i] = acc[1][i];
            }
        }
        CTA_SYNC();
        if (tid < 32) {
            int bb = tid >> 4, c = (tid & 15) * 2;
            float s0 = 0.f, s1 = 0.f;
#pragma unroll
            for (int w = 0; w < NWARP; w++) { s0 += s_qpart[w][bb][c]; s1 += s_qpart[w][bb][c + 1]; }
            unsigned long long v = ((unsigned long long)epoch << 32) | pack_bf16(s0, s1);
            asm volatile("st.relaxed.gpu.global.u64 [%0], %1;" ::"l"(&g_q64[(bb * (HQ * DH) + cta * 32 + c) >> 1]), "l"(v) : "memory");
        }
    }
    TS(2);

    uint32_t qa[8][2];
    {
        int hl = lane >> 2;
        const unsigned long long* qp = g_q64 + ((b * (HQ * DH) + (kvh * 4 + (hl & 3)) * DH + (lane & 3) * 2) >> 1);
        for (int tries = 0; tries < (1 << 20); tries++) {
            bool ok = true;
#pragma unroll
            for (int ks = 0; ks < 8; ks++) {
                unsigned long long v0, v1;
                asm volatile("ld.relaxed.gpu.global.u64 %0, [%1];" : "=l"(v0) : "l"(qp + ks * 8) : "memory");
                asm volatile("ld.relaxed.gpu.global.u64 %0, [%1];" : "=l"(v1) : "l"(qp + ks * 8 + 4) : "memory");
                ok = ok && ((unsigned)(v0 >> 32) == epoch) && ((unsigned)(v1 >> 32) == epoch);
                qa[ks][0] = hl < 4 ? (uint32_t)v0 : 0u;
                qa[ks][1] = hl < 4 ? (uint32_t)v1 : 0u;
            }
            if (__all_sync(0xffffffffu, ok)) break;
            __nanosleep(400);
        }
    }
    TS(3);
    float oacc[16][4];
#pragma unroll
    for (int j = 0; j < 16; j++) { oacc[j][0] = 0.f; oacc[j][1] = 0.f; oacc[j][2] = 0.f; oacc[j][3] = 0.f; }
    float m_run = -INFINITY, l_run = 0.f;
    const float scale = 0.08838834764831845f;
    const float LOG2E = 1.4426950408889634f;

    const int lrow = lane & 7, lmat = lane >> 3;
    const int k_row = (lmat >> 1) * 8 + lrow;
    const int k_cofs = lmat & 1;
    const int v_row = (lmat & 1) * 8 + lrow;
    const int v_cofs = lmat >> 1;

#pragma unroll
    for (int it = 0; it < NBLK; it++) {
        const int s = it % NSTAGE;
        const uint32_t parity = (it / NSTAGE) & 1;
        const uint32_t st = ring_w + s * STAGE_BYTES;
        mbar_wait(bar_w + s * 8, parity);

        float sc[2][4];
#pragma unroll
        for (int j = 0; j < 2; j++) { sc[j][0] = 0.f; sc[j][1] = 0.f; sc[j][2] = 0.f; sc[j][3] = 0.f; }
#pragma unroll
        for (int ks = 0; ks < 8; ks++) {
            int chunk = (ks & 3) * 2 + k_cofs;
            uint32_t addr = st + (ks >> 2) * 2048 + k_row * 128 + ((chunk ^ (k_row & 7)) << 4);
            uint32_t r0, r1, r2, r3;
            ldsm_x4(addr, r0, r1, r2, r3);
            mma16816(sc[0], qa[ks][0], 0u, qa[ks][1], 0u, r0, r1);
            mma16816(sc[1], qa[ks][0], 0u, qa[ks][1], 0u, r2, r3);
        }
        float v00 = bf16r(bf16r(sc[0][0]) * scale), v01 = bf16r(bf16r(sc[0][1]) * scale);
        float v10 = bf16r(bf16r(sc[1][0]) * scale), v11 = bf16r(bf16r(sc[1][1]) * scale);
        float mx = fmaxf(fmaxf(v00, v01), fmaxf(v10, v11));
        mx = fmaxf(mx, __shfl_xor_sync(0xffffffffu, mx, 1));
        mx = fmaxf(mx, __shfl_xor_sync(0xffffffffu, mx, 2));
        float m_new = fmaxf(m_run, mx);
        float corr = exp2f((m_run - m_new) * LOG2E);
        float p00 = exp2f((v00 - m_new) * LOG2E), p01 = exp2f((v01 - m_new) * LOG2E);
        float p10 = exp2f((v10 - m_new) * LOG2E), p11 = exp2f((v11 - m_new) * LOG2E);
        l_run = l_run * corr + (p00 + p01 + p10 + p11);
        m_run = m_new;
        uint32_t pa0 = pack_bf16(p00, p01), pa2 = pack_bf16(p10, p11);
#pragma unroll
        for (int j = 0; j < 16; j++) { oacc[j][0] *= corr; oacc[j][1] *= corr; }
#pragma unroll
        for (int jj = 0; jj < 8; jj++) {
            int chunk = (jj & 3) * 2 + v_cofs;
            uint32_t addr = st + 4096 + (jj >> 2) * 2048 + v_row * 128 + ((chunk ^ (v_row & 7)) << 4);
            uint32_t r0, r1, r2, r3;
            ldsm_x4_t(addr, r0, r1, r2, r3);
            mma16816(oacc[2 * jj], pa0, 0u, pa2, 0u, r0, r1);
            mma16816(oacc[2 * jj + 1], pa0, 0u, pa2, 0u, r2, r3);
        }
        __syncwarp();
        if (lane == 0 && it + NSTAGE < NBLK) issue_stage(it + NSTAGE);
    }
    TS(4);
    l_run += __shfl_xor_sync(0xffffffffu, l_run, 1);
    l_run += __shfl_xor_sync(0xffffffffu, l_run, 2);

    CTA_SYNC();
    float* r_o = reinterpret_cast<float*>(ring);
    float* r_m = reinterpret_cast<float*>(ring + 16384);
    float* r_l = r_m + 32;
    if (lane < 16) {
        int hl = lane >> 2;
#pragma unroll
        for (int j = 0; j < 16; j++) {
            float2 v = make_float2(oacc[j][0], oacc[j][1]);
            *reinterpret_cast<float2*>(&r_o[(warp * 4 + hl) * DH + j * 8 + (lane & 3) * 2]) = v;
        }
        if ((lane & 3) == 0) { r_m[warp * 4 + hl] = m_run; r_l[warp * 4 + hl] = l_run; }
    }
    CTA_SYNC();
    {
        int hl = tid >> 6, d = (tid & 63) * 2;
        float mm = -INFINITY;
#pragma unroll
        for (int w = 0; w < NWARP; w++) mm = fmaxf(mm, r_m[w * 4 + hl]);
        float o0 = 0.f, o1 = 0.f, ll = 0.f;
#pragma unroll
        for (int w = 0; w < NWARP; w++) {
            float c = exp2f((r_m[w * 4 + hl] - mm) * LOG2E);
            float2 v = *reinterpret_cast<float2*>(&r_o[(w * 4 + hl) * DH + d]);
            o0 += c * v.x; o1 += c * v.y; ll += c * r_l[w * 4 + hl];
        }
        int pidx = (cta * 4 + hl);
        *reinterpret_cast<float2*>(&g_po[(size_t)pidx * DH + d]) = make_float2(o0, o1);
        if ((tid & 63) == 0) { g_pm[pidx] = mm; g_pl[pidx] = ll; }
    }
    TS(5);
    grid_barrier();
    TS(6);

    {
        int head = cta >> 2;
        int kv = head >> 2, hl = head & 3;
        {
            int bb = tid >> 7, d = tid & 127;
            int base = ((bb * 8 + kv) * NSPLIT) * 4 + hl;
            float pm[NSPLIT], pl[NSPLIT], po[NSPLIT];
#pragma unroll
            for (int s = 0; s < NSPLIT; s++) {
                pm[s] = __ldcg(&g_pm[base + s * 4]);
                pl[s] = __ldcg(&g_pl[base + s * 4]);
                po[s] = __ldcg(&g_po[(size_t)(base + s * 4) * DH + d]);
            }
            float mm = -INFINITY;
#pragma unroll
            for (int s = 0; s < NSPLIT; s++) mm = fmaxf(mm, pm[s]);
            float oo = 0.f, ll = 0.f;
#pragma unroll
            for (int s = 0; s < NSPLIT; s++) {
                float c = exp2f((pm[s] - mm) * LOG2E);
                oo += c * po[s]; ll += c * pl[s];
            }
            s_vec[tid] = bf16r(oo / ll);
        }
        CTA_SYNC();
        float a[2][8];
#pragma unroll
        for (int j = 0; j < 8; j++) { a[0][j] = 0.f; a[1][j] = 0.f; }
#pragma unroll
        for (int i = 0; i < 8; i++) {
            int r = (tid >> 4) + 16 * i;
            float o0 = s_vec[r], o1 = s_vec[128 + r];
            uint32_t w[4] = {wov[i].x, wov[i].y, wov[i].z, wov[i].w};
#pragma unroll
            for (int j = 0; j < 4; j++) {
                float lo = bf_lo(w[j]), hi = bf_hi(w[j]);
                a[0][2 * j] += o0 * lo; a[0][2 * j + 1] += o0 * hi;
                a[1][2 * j] += o1 * lo; a[1][2 * j + 1] += o1 * hi;
            }
        }
#pragma unroll
        for (int j = 0; j < 8; j++) {
            a[0][j] += __shfl_xor_sync(0xffffffffu, a[0][j], 16);
            a[1][j] += __shfl_xor_sync(0xffffffffu, a[1][j], 16);
        }
        float* s_p = reinterpret_cast<float*>(ring);
        if (lane < 16) {
#pragma unroll
            for (int bb = 0; bb < 2; bb++) {
                float4* dst = reinterpret_cast<float4*>(&s_p[(warp * 2 + bb) * 128 + lane * 8]);
                dst[0] = make_float4(a[bb][0], a[bb][1], a[bb][2], a[bb][3]);
                dst[1] = make_float4(a[bb][4], a[bb][5], a[bb][6], a[bb][7]);
            }
        }
        CTA_SYNC();
        if (tid < 64) {
            int bb = tid >> 5, c4 = (tid & 31) * 4;
            float4 acc = make_float4(0.f, 0.f, 0.f, 0.f);
#pragma unroll
            for (int w = 0; w < NWARP; w++) {
                float4 v = *reinterpret_cast<float4*>(&s_p[(w * 2 + bb) * 128 + c4]);
                acc.x += v.x; acc.y += v.y; acc.z += v.z; acc.w += v.w;
            }
            red_v4(&g_attn_acc[bb * 512 + (cta & 3) * 128 + c4], acc.x, acc.y, acc.z, acc.w);
        }
    }
    TS(7);
    grid_barrier();
    TS(8);

    float h00, h01, h10, h11;
    {
        float2 aa = __ldcg(reinterpret_cast<const float2*>(&g_attn_acc[2 * tid]));
        float2 ab = __ldcg(reinterpret_cast<const float2*>(&g_attn_acc[512 + 2 * tid]));
        h00 = bf16r(bf_lo(xv0) + bf16r(aa.x)); h01 = bf16r(bf_hi(xv0) + bf16r(aa.y));
        h10 = bf16r(bf_lo(xv1) + bf16r(ab.x)); h11 = bf16r(bf_hi(xv1) + bf16r(ab.y));
        s_vec[2 * tid] = h00; s_vec[2 * tid + 1] = h01;
        s_vec[512 + 2 * tid] = h10; s_vec[512 + 2 * tid + 1] = h11;
        CTA_SYNC();
        layernorm_2x512(s_vec, s_red, tid);
        if (cta < 112) {
            float f[2][8];
#pragma unroll
            for (int j = 0; j < 8; j++) { f[0][j] = 0.f; f[1][j] = 0.f; }
#pragma unroll
            for (int i = 0; i < 4; i++) {
                int r = (tid >> 1) + 128 * i;
                float n0 = s_vec[r], n1 = s_vec[512 + r];
                uint32_t w[4] = {w1v[i].x, w1v[i].y, w1v[i].z, w1v[i].w};
#pragma unroll
                for (int j = 0; j < 4; j++) {
                    float lo = bf_lo(w[j]), hi = bf_hi(w[j]);
                    f[0][2 * j] += n0 * lo; f[0][2 * j + 1] += n0 * hi;
                    f[1][2 * j] += n1 * lo; f[1][2 * j + 1] += n1 * hi;
                }
            }
#pragma unroll
            for (int o = 2; o < 32; o <<= 1) {
#pragma unroll
                for (int j = 0; j < 8; j++) {
                    f[0][j] += __shfl_xor_sync(0xffffffffu, f[0][j], o);
                    f[1][j] += __shfl_xor_sync(0xffffffffu, f[1][j], o);
                }
            }
            float* s_fp = reinterpret_cast<float*>(ring);
            if (lane < 2) {
#pragma unroll
                for (int j = 0; j < 8; j++) {
                    s_fp[(warp * 2 + 0) * 16 + lane * 8 + j] = f[0][j];
                    s_fp[(warp * 2 + 1) * 16 + lane * 8 + j] = f[1][j];
                }
            }
            CTA_SYNC();
            if (tid < 32) {
                int bb = tid >> 4, c = tid & 15;
                float sacc = 0.f;
#pragma unroll
                for (int w = 0; w < NWARP; w++) sacc += s_fp[(w * 2 + bb) * 16 + c];
                float bias = __bfloat162float(b1[cta * 16 + c]);
                float hh = bf16r(bf16r(sacc) + bias);
                s_f[tid] = bf16r(gelu_tanh(hh));
            }
            CTA_SYNC();
            float a[2][8];
#pragma unroll
            for (int j = 0; j < 8; j++) { a[0][j] = 0.f; a[1][j] = 0.f; }
#pragma unroll
            for (int i = 0; i < 4; i++) {
                int r = (tid >> 6) + 4 * i;
                float f0 = s_f[r], f1 = s_f[16 + r];
                uint32_t w[4] = {w2v[i].x, w2v[i].y, w2v[i].z, w2v[i].w};
#pragma unroll
                for (int j = 0; j < 4; j++) {
                    float lo = bf_lo(w[j]), hi = bf_hi(w[j]);
                    a[0][2 * j] += f0 * lo; a[0][2 * j + 1] += f0 * hi;
                    a[1][2 * j] += f1 * lo; a[1][2 * j + 1] += f1 * hi;
                }
            }
            float* s_p = reinterpret_cast<float*>(ring) + 1024;
            {
                int g = tid >> 6, c8 = (tid & 63) * 8;
#pragma unroll
                for (int bb = 0; bb < 2; bb++) {
                    float4* dst = reinterpret_cast<float4*>(&s_p[(g * 2 + bb) * 512 + c8]);
                    dst[0] = make_float4(a[bb][0], a[bb][1], a[bb][2], a[bb][3]);
                    dst[1] = make_float4(a[bb][4], a[bb][5], a[bb][6], a[bb][7]);
                }
            }
            CTA_SYNC();
            {
                int bb = tid >> 7, c4 = (tid & 127) * 4;
                float4 acc = make_float4(0.f, 0.f, 0.f, 0.f);
#pragma unroll
                for (int g = 0; g < 4; g++) {
                    float4 v = *reinterpret_cast<float4*>(&s_p[(g * 2 + bb) * 512 + c4]);
                    acc.x += v.x; acc.y += v.y; acc.z += v.z; acc.w += v.w;
                }
                red_v4(&g_out_acc[(cta & 3) * 1024 + bb * 512 + c4], acc.x, acc.y, acc.z, acc.w);
            }
        }
    }
    TS(9);
    __shared__ unsigned s_last;
    CTA_SYNC();
    if (tid == 0) {
        __threadfence();
        unsigned old = atomicAdd(&g_done, 1u);
        s_last = ((old % NCTA) == NCTA - 1) ? 1u : 0u;
        __threadfence();
    }
    CTA_SYNC();
    if (s_last) {
        float2 oa = make_float2(0.f, 0.f), ob = make_float2(0.f, 0.f);
#pragma unroll
        for (int c = 0; c < 4; c++) {
            float2 va = __ldcg(reinterpret_cast<const float2*>(&g_out_acc[c * 1024 + 2 * tid]));
            float2 vb = __ldcg(reinterpret_cast<const float2*>(&g_out_acc[c * 1024 + 512 + 2 * tid]));
            oa.x += va.x; oa.y += va.y; ob.x += vb.x; ob.y += vb.y;
        }
        uint32_t bb = *reinterpret_cast<const uint32_t*>(b2 + 2 * tid);
        float bl = bf_lo(bb), bhh = bf_hi(bb);
        float r00 = h00 + bf16r(bf16r(oa.x) + bl), r01 = h01 + bf16r(bf16r(oa.y) + bhh);
        float r10 = h10 + bf16r(bf16r(ob.x) + bl), r11 = h11 + bf16r(bf16r(ob.y) + bhh);
        *reinterpret_cast<uint32_t*>(out + 2 * tid) = pack_bf16(r00, r01);
        *reinterpret_cast<uint32_t*>(out + 512 + 2 * tid) = pack_bf16(r10, r11);
        for (int i = tid; i < NB * DM; i += NTHREADS) g_attn_acc[i] = 0.f;
        for (int i = tid; i < 4 * NB * DM; i += NTHREADS) g_out_acc[i] = 0.f;
        if (tid == 0) g_epoch = epoch;
    }
    TS(10);
}

typedef CUresult (*PFN_encodeTiled)(CUtensorMap*, CUtensorMapDataType, cuuint32_t, void*, const cuuint64_t*,
                                    const cuuint64_t*, const cuuint32_t*, const cuuint32_t*, CUtensorMapInterleave,
                                    CUtensorMapSwizzle, CUtensorMapL2promotion, CUtensorMapFloatOOBfill);

}

extern "C" void kernel_launch(void* const* d_in, const int* in_sizes, int n_in, void* d_out, int out_size) {
    static PFN_encodeTiled enc = nullptr;
    if (!enc) {
        void* fn = nullptr;
        cudaDriverEntryPointQueryResult qres;
        cudaGetDriverEntryPoint("cuTensorMapEncodeTiled", &fn, cudaEnableDefault, &qres);
        enc = (PFN_encodeTiled)fn;
        cudaFuncSetAttribute(fused_kernel, cudaFuncAttributeMaxDynamicSharedMemorySize, SMEM_BYTES);
    }
    CUtensorMap mapK, mapV;
    cuuint64_t gdim[2] = {(cuuint64_t)DH, (cuuint64_t)NB * HKV * SK};
    cuuint64_t gstr[1] = {(cuuint64_t)DH * 2};
    cuuint32_t box[2] = {64, 16};
    cuuint32_t estr[2] = {1, 1};
    enc(&mapK, CU_TENSOR_MAP_DATA_TYPE_BFLOAT16, 2, d_in[1], gdim, gstr, box, estr, CU_TENSOR_MAP_INTERLEAVE_NONE,
        CU_TENSOR_MAP_SWIZZLE_128B, CU_TENSOR_MAP_L2_PROMOTION_L2_128B, CU_TENSOR_MAP_FLOAT_OOB_FILL_NONE);
    enc(&mapV, CU_TENSOR_MAP_DATA_TYPE_BFLOAT16, 2, d_in[2], gdim, gstr, box, estr, CU_TENSOR_MAP_INTERLEAVE_NONE,
        CU_TENSOR_MAP_SWIZZLE_128B, CU_TENSOR_MAP_L2_PROMOTION_L2_128B, CU_TENSOR_MAP_FLOAT_OOB_FILL_NONE);
    fused_kernel<<<NCTA, NTHREADS, SMEM_BYTES>>>(
        mapK, mapV, (const __nv_bfloat16*)d_in[0], (const __nv_bfloat16*)d_in[3], (const __nv_bfloat16*)d_in[4],
        (const __nv_bfloat16*)d_in[6], (const __nv_bfloat16*)d_in[7], (const __nv_bfloat16*)d_in[8],
        (const __nv_bfloat16*)d_in[9], (__nv_bfloat16*)d_out);
}
```

```cpp
#include <cuda_runtime.h>
#include <cuda_bf16.h>
#include <cuda.h>
#include <stdint.h>

namespace {

constexpr int NB = 2, DM = 512, HQ = 32, HKV = 8, SK = 8192, DH = 128, FF = 1792;
constexpr int NCTA = 128, NSPLIT = 8, KEYS_PER_CTA = SK / NSPLIT;
constexpr int NWARP = 8, NTHREADS = NWARP * 32;
constexpr int NSTAGE = 3;
#define REST_MODE 1
#define EARLY_W 0
#define QTRIES (1 << 20)
#define L2PF 0
#define LATE_W 0
#define PF_IT 1
#define QSLEEP 400
#define PRE_STAGES 0
constexpr int STAGE_BYTES = 8192;
constexpr int NBLK = KEYS_PER_CTA / (16 * NWARP);
constexpr int RING_BYTES = NWARP * NSTAGE * STAGE_BYTES;
constexpr int SMEM_BYTES = RING_BYTES + 4096 + 2048 + 1024;

__device__ unsigned long long g_q64[NB * HQ * DH / 2];
__device__ unsigned g_epoch;
__device__ unsigned long long g_pm[16 * NSPLIT * 4];
__device__ unsigned long long g_pl[16 * NSPLIT * 4];
__device__ unsigned long long g_po[16 * NSPLIT * 4 * DH];
__device__ float g_attn_acc[NB * DM];
__device__ float g_out_acc[4 * NB * DM];
__device__ unsigned g_bar;
__device__ unsigned g_done;

#define TS(i)
#define CTA_SYNC() asm volatile("bar.sync 1, 256;" ::: "memory")
__device__ __forceinline__ uint32_t smem_u32(const void* p) {
    return (uint32_t)__cvta_generic_to_shared(p);
}
__device__ __forceinline__ float bf16r(float x) {
    return __bfloat162float(__float2bfloat16_rn(x));
}
__device__ __forceinline__ uint32_t pack_bf16(float lo, float hi) {
    __nv_bfloat162 v = __floats2bfloat162_rn(lo, hi);
    return *reinterpret_cast<uint32_t*>(&v);
}
__device__ __forceinline__ float bf_lo(uint32_t v) { return __uint_as_float(v << 16); }
__device__ __forceinline__ float bf_hi(uint32_t v) { return __uint_as_float(v & 0xffff0000u); }

__device__ __forceinline__ void mbar_init(uint32_t bar, uint32_t cnt) {
    asm volatile("mbarrier.init.shared::cta.b64 [%0], %1;" ::"r"(bar), "r"(cnt) : "memory");
}
__device__ __forceinline__ void mbar_expect_tx(uint32_t bar, uint32_t bytes) {
    asm volatile("mbarrier.arrive.expect_tx.shared::cta.b64 _, [%0], %1;" ::"r"(bar), "r"(bytes) : "memory");
}
__device__ __forceinline__ void mbar_wait(uint32_t bar, uint32_t parity) {
    for (int i = 0; i < (1 << 22); i++) {
        uint32_t ok;
        asm volatile(
            "{\n"
            ".reg .pred p;\n"
            "mbarrier.try_wait.parity.shared::cta.b64 p, [%1], %2;\n"
            "selp.u32 %0, 1, 0, p;\n"
            "}\n" : "=r"(ok) : "r"(bar), "r"(parity) : "memory");
        if (ok) break;
    }
}
__device__ __forceinline__ void tma_2d(uint32_t dst, const CUtensorMap* map, uint32_t bar, int c0, int c1) {
    asm volatile(
        "cp.async.bulk.tensor.2d.shared::cluster.global.mbarrier::complete_tx::bytes [%0], [%1, {%3, %4}], [%2];"
        ::"r"(dst), "l"(map), "r"(bar), "r"(c0), "r"(c1) : "memory");
}
__device__ __forceinline__ void ldsm_x4(uint32_t addr, uint32_t& r0, uint32_t& r1, uint32_t& r2, uint32_t& r3) {
    asm volatile("ldmatrix.sync.aligned.m8n8.x4.shared.b16 {%0,%1,%2,%3}, [%4];"
                 : "=r"(r0), "=r"(r1), "=r"(r2), "=r"(r3) : "r"(addr) : "memory");
}
__device__ __forceinline__ void ldsm_x4_t(uint32_t addr, uint32_t& r0, uint32_t& r1, uint32_t& r2, uint32_t& r3) {
    asm volatile("ldmatrix.sync.aligned.m8n8.x4.trans.shared.b16 {%0,%1,%2,%3}, [%4];"
                 : "=r"(r0), "=r"(r1), "=r"(r2), "=r"(r3) : "r"(addr) : "memory");
}
__device__ __forceinline__ void mma16816(float* c, uint32_t a0, uint32_t a1, uint32_t a2, uint32_t a3,
                                         uint32_t b0, uint32_t b1) {
    asm volatile(
        "mma.sync.aligned.m16n8k16.row.col.f32.bf16.bf16.f32 {%0,%1,%2,%3}, {%4,%5,%6,%7}, {%8,%9}, {%0,%1,%2,%3};"
        : "+f"(c[0]), "+f"(c[1]), "+f"(c[2]), "+f"(c[3])
        : "r"(a0), "r"(a1), "r"(a2), "r"(a3), "r"(b0), "r"(b1));
}
__device__ __forceinline__ unsigned ld_acquire(const unsigned* p) {
    unsigned v;
    asm volatile("ld.acquire.gpu.global.u32 %0, [%1];" : "=r"(v) : "l"(p) : "memory");
    return v;
}
__device__ __forceinline__ uint4 ldg_nc_v4(const void* p) {
    uint4 v;
    asm volatile("ld.global.nc.L1::no_allocate.v4.u32 {%0,%1,%2,%3}, [%4];"
                 : "=r"(v.x), "=r"(v.y), "=r"(v.z), "=r"(v.w) : "l"(p));
    return v;
}
__device__ __forceinline__ uint32_t ldg_nc_u32(const void* p) {
    uint32_t v;
    asm volatile("ld.global.nc.L1::no_allocate.u32 %0, [%1];" : "=r"(v) : "l"(p));
    return v;
}

__device__ __forceinline__ void red_v4(float* p, float a, float b, float c, float d) {
    asm volatile("red.global.add.v4.f32 [%0], {%1,%2,%3,%4};" ::"l"(p), "f"(a), "f"(b), "f"(c), "f"(d) : "memory");
}

__device__ __forceinline__ void st_tag(unsigned long long* p, float v, unsigned tag) {
    unsigned long long w = ((unsigned long long)tag << 32) | __float_as_uint(v);
    asm volatile("st.relaxed.gpu.global.u64 [%0], %1;" ::"l"(p), "l"(w) : "memory");
}
__device__ __forceinline__ unsigned long long ld_tag(const unsigned long long* p) {
    unsigned long long w;
    asm volatile("ld.relaxed.gpu.global.u64 %0, [%1];" : "=l"(w) : "l"(p) : "memory");
    return w;
}

__device__ __forceinline__ void grid_barrier() {
    CTA_SYNC();
    if (threadIdx.x == 0) {
        __threadfence();
        unsigned old = atomicAdd(&g_bar, 1u);
        unsigned target = (old / NCTA + 1u) * NCTA;
        unsigned iters = 0;
        while ((int)(ld_acquire(&g_bar) - target) < 0) {
            if (++iters > 2000000u) break;
        }
        __threadfence();
    }
    CTA_SYNC();
}

__device__ __forceinline__ void layernorm_2x512(float* v, float* red, int tid) {
    int warp = tid >> 5, lane = tid & 31;
    float a0 = v[2 * tid], a1 = v[2 * tid + 1], b0 = v[512 + 2 * tid], b1 = v[512 + 2 * tid + 1];
    float sa = a0 + a1, sb = b0 + b1;
#pragma unroll
    for (int o = 16; o > 0; o >>= 1) {
        sa += __shfl_xor_sync(0xffffffffu, sa, o);
        sb += __shfl_xor_sync(0xffffffffu, sb, o);
    }
    if (lane == 0) { red[warp] = sa; red[8 + warp] = sb; }
    CTA_SYNC();
    float ma = 0.f, mb = 0.f;
#pragma unroll
    for (int w = 0; w < 8; w++) { ma += red[w]; mb += red[8 + w]; }
    ma *= (1.f / 512.f); mb *= (1.f / 512.f);
    float da0 = a0 - ma, da1 = a1 - ma, db0 = b0 - mb, db1 = b1 - mb;
    float va = da0 * da0 + da1 * da1, vb = db0 * db0 + db1 * db1;
#pragma unroll
    for (int o = 16; o > 0; o >>= 1) {
        va += __shfl_xor_sync(0xffffffffu, va, o);
        vb += __shfl_xor_sync(0xffffffffu, vb, o);
    }
    CTA_SYNC();
    if (lane == 0) { red[16 + warp] = va; red[24 + warp] = vb; }
    CTA_SYNC();
    va = 0.f; vb = 0.f;
#pragma unroll
    for (int w = 0; w < 8; w++) { va += red[16 + w]; vb += red[24 + w]; }
    va = bf16r(va * (1.f / 512.f)); vb = bf16r(vb * (1.f / 512.f));
    float mra = bf16r(ma), mrb = bf16r(mb);
    float sda = bf16r(sqrtf(bf16r(va + 1e-5f))), sdb = bf16r(sqrtf(bf16r(vb + 1e-5f)));
    v[2 * tid] = bf16r(bf16r(a0 - mra) / sda);
    v[2 * tid + 1] = bf16r(bf16r(a1 - mra) / sda);
    v[512 + 2 * tid] = bf16r(bf16r(b0 - mrb) / sdb);
    v[512 + 2 * tid + 1] = bf16r(bf16r(b1 - mrb) / sdb);
    CTA_SYNC();
}

__device__ __forceinline__ float gelu_tanh(float x) {
    const float k0 = 0.7978845608028654f, k1 = 0.044715f;
    float inner = k0 * (x + k1 * x * x * x);
    return 0.5f * x * (1.f + tanhf(inner));
}

__global__ void __launch_bounds__(NTHREADS, 1)
fused_kernel(const __grid_constant__ CUtensorMap mapK, const __grid_constant__ CUtensorMap mapV,
             const __nv_bfloat16* __restrict__ x, const __nv_bfloat16* __restrict__ wq,
             const __nv_bfloat16* __restrict__ wo, const __nv_bfloat16* __restrict__ w1,
             const __nv_bfloat16* __restrict__ b1, const __nv_bfloat16* __restrict__ w2,
             const __nv_bfloat16* __restrict__ b2, __nv_bfloat16* __restrict__ out) {
    extern __shared__ __align__(1024) uint8_t smem_raw[];
    uint8_t* smem = smem_raw + ((1024u - (smem_u32(smem_raw) & 1023u)) & 1023u);
    uint8_t* ring = smem;
    uint64_t* bars = reinterpret_cast<uint64_t*>(smem + RING_BYTES);
    float* s_vec = reinterpret_cast<float*>(smem + RING_BYTES + 256);
    float* s_red = reinterpret_cast<float*>(smem + RING_BYTES + 256 + 4096);
    float* s_o = s_red + 64;
    float* s_f = s_o + 64;

    const int tid = threadIdx.x, warp = tid >> 5, lane = tid & 31;
    const int cta = blockIdx.x;
    const int bh = cta >> 3, split = cta & 7;
    const int b = bh >> 3, kvh = bh & 7;

    TS(0);
    const uint32_t ring_w = smem_u32(ring) + warp * (NSTAGE * STAGE_BYTES);
    const uint32_t bar_w = smem_u32(bars) + warp * (NSTAGE * 8);
    if (lane == 0) {
#pragma unroll
        for (int s = 0; s < NSTAGE; s++) mbar_init(bar_w + s * 8, 1);
        asm volatile("fence.mbarrier_init.release.cluster;" ::: "memory");
    }
    __syncwarp();
    const unsigned epoch = __ldcg(&g_epoch) + 1u;
    uint32_t xv0 = ldg_nc_u32(x + 2 * tid);
    uint32_t xv1 = ldg_nc_u32(x + 512 + 2 * tid);
    uint4 wqv[8];
    {
        const __nv_bfloat16* p = wq + (size_t)(tid >> 2) * (HQ * DH) + cta * 32 + (tid & 3) * 8;
#pragma unroll
        for (int i = 0; i < 8; i++) wqv[i] = ldg_nc_v4(p + (size_t)i * 64 * (HQ * DH));
    }
    const int row0 = bh * SK + split * KEYS_PER_CTA + warp * 16;
    auto issue_stage = [&](int blk) {
        const int s = blk % NSTAGE;
        uint32_t dst = ring_w + s * STAGE_BYTES;
        uint32_t bar = bar_w + s * 8;
        int r = row0 + blk * 128;
        mbar_expect_tx(bar, STAGE_BYTES);
        tma_2d(dst, &mapK, bar, 0, r);
        tma_2d(dst + 2048, &mapK, bar, 64, r);
        tma_2d(dst + 4096, &mapV, bar, 0, r);
        tma_2d(dst + 6144, &mapV, bar, 64, r);
    };
    if (lane == 0) {
#pragma unroll
        for (int s = 0; s < PRE_STAGES; s++) issue_stage(s);
    }
    uint4 wov[8];
    uint4 w1v[4];
    uint4 w2v[4];
    const __nv_bfloat16* wo_p = wo + (size_t)((cta >> 2) * 128 + (tid >> 4)) * DM + (cta & 3) * 128 + (tid & 15) * 8;
    const int fcta = cta < 112 ? cta : 0;
    const __nv_bfloat16* w1_p = w1 + (size_t)(tid >> 1) * FF + fcta * 16 + (tid & 1) * 8;
    const __nv_bfloat16* w2_p = w2 + (size_t)(fcta * 16 + (tid >> 6)) * DM + (tid & 63) * 8;

    TS(1);
    s_vec[2 * tid] = bf_lo(xv0); s_vec[2 * tid + 1] = bf_hi(xv0);
    s_vec[512 + 2 * tid] = bf_lo(xv1); s_vec[512 + 2 * tid + 1] = bf_hi(xv1);
    CTA_SYNC();
    layernorm_2x512(s_vec, s_red, tid);

    {
        float acc[2][8];
#pragma unroll
        for (int i = 0; i < 8; i++) { acc[0][i] = 0.f; acc[1][i] = 0.f; }
#pragma unroll
        for (int i = 0; i < 8; i++) {
            int r = (tid >> 2) + i * 64;
            float x0 = s_vec[r], x1 = s_vec[512 + r];
            uint32_t w[4] = {wqv[i].x, wqv[i].y, wqv[i].z, wqv[i].w};
#pragma unroll
            for (int j = 0; j < 4; j++) {
                float lo = bf_lo(w[j]), hi = bf_hi(w[j]);
                acc[0][2 * j] += x0 * lo; acc[0][2 * j + 1] += x0 * hi;
                acc[1][2 * j] += x1 * lo; acc[1][2 * j + 1] += x1 * hi;
            }
        }
        if (lane == 0) {
#pragma unroll
            for (int s = PRE_STAGES; s < NSTAGE; s++) issue_stage(s);
        }
#pragma unroll
        for (int o = 4; o < 32; o <<= 1) {
#pragma unroll
            for (int i = 0; i < 8; i++) {
                acc[0][i] += __shfl_xor_sync(0xffffffffu, acc[0][i], o);
                acc[1][i] += __shfl_xor_sync(0xffffffffu, acc[1][i], o);
            }
        }
        __shared__ float s_qpart[NWARP][2][32];
        if (lane < 4) {
#pragma unroll
            for (int i = 0; i < 8; i++) {
                s_qpart[warp][0][lane * 8 + i] = acc[0][i];
                s_qpart[warp][1][lane * 8 + i] = acc[1][i];
            }
        }
        CTA_SYNC();
        if (tid < 32) {
            int bb = tid >> 4, c = (tid & 15) * 2;
            float s0 = 0.f, s1 = 0.f;
#pragma unroll
            for (int w = 0; w < NWARP; w++) { s0 += s_qpart[w][bb][c]; s1 += s_qpart[w][bb][c + 1]; }
            unsigned long long v = ((unsigned long long)epoch << 32) | pack_bf16(s0, s1);
            asm volatile("st.relaxed.gpu.global.u64 [%0], %1;" ::"l"(&g_q64[(bb * (HQ * DH) + cta * 32 + c) >> 1]), "l"(v) : "memory");
        }
    }
    TS(2);

    uint32_t qa[8][2];
    {
        int hl = lane >> 2;
        const unsigned long long* qp = g_q64 + ((b * (HQ * DH) + (kvh * 4 + (hl & 3)) * DH + (lane & 3) * 2) >> 1);
        for (int tries = 0; tries < (1 << 20); tries++) {
            bool ok = true;
#pragma unroll
            for (int ks = 0; ks < 8; ks++) {
                unsigned long long v0, v1;
                asm volatile("ld.relaxed.gpu.global.u64 %0, [%1];" : "=l"(v0) : "l"(qp + ks * 8) : "memory");
                asm volatile("ld.relaxed.gpu.global.u64 %0, [%1];" : "=l"(v1) : "l"(qp + ks * 8 + 4) : "memory");
                ok = ok && ((unsigned)(v0 >> 32) == epoch) && ((unsigned)(v1 >> 32) == epoch);
                qa[ks][0] = hl < 4 ? (uint32_t)v0 : 0u;
                qa[ks][1] = hl < 4 ? (uint32_t)v1 : 0u;
            }
            if (__all_sync(0xffffffffu, ok)) break;
            __nanosleep(QSLEEP);
        }
    }
    TS(3);
    float oacc[16][4];
#pragma unroll
    for (int j = 0; j < 16; j++) { oacc[j][0] = 0.f; oacc[j][1] = 0.f; oacc[j][2] = 0.f; oacc[j][3] = 0.f; }
    float m_run = -INFINITY, l_run = 0.f;
    const float scale = 0.08838834764831845f;
    const float LOG2E = 1.4426950408889634f;

    const int lrow = lane & 7, lmat = lane >> 3;
    const int k_row = (lmat >> 1) * 8 + lrow;
    const int k_cofs = lmat & 1;
    const int v_row = (lmat & 1) * 8 + lrow;
    const int v_cofs = lmat >> 1;

#pragma unroll
    for (int it = 0; it < NBLK; it++) {
        wov[it] = ldg_nc_v4(wo_p + (size_t)it * 16 * DM);
        if (it < 4) w1v[it] = ldg_nc_v4(w1_p + (size_t)it * 128 * FF);
        else w2v[it - 4] = ldg_nc_v4(w2_p + (size_t)(it - 4) * 4 * DM);
        const int s = it % NSTAGE;
        const uint32_t parity = (it / NSTAGE) & 1;
        const uint32_t st = ring_w + s * STAGE_BYTES;
        mbar_wait(bar_w + s * 8, parity);

        float sc[2][4];
#pragma unroll
        for (int j = 0; j < 2; j++) { sc[j][0] = 0.f; sc[j][1] = 0.f; sc[j][2] = 0.f; sc[j][3] = 0.f; }
#pragma unroll
        for (int ks = 0; ks < 8; ks++) {
            int chunk = (ks & 3) * 2 + k_cofs;
            uint32_t addr = st + (ks >> 2) * 2048 + k_row * 128 + ((chunk ^ (k_row & 7)) << 4);
            uint32_t r0, r1, r2, r3;
            ldsm_x4(addr, r0, r1, r2, r3);
            mma16816(sc[0], qa[ks][0], 0u, qa[ks][1], 0u, r0, r1);
            mma16816(sc[1], qa[ks][0], 0u, qa[ks][1], 0u, r2, r3);
        }
        float v00 = bf16r(bf16r(sc[0][0]) * scale), v01 = bf16r(bf16r(sc[0][1]) * scale);
        float v10 = bf16r(bf16r(sc[1][0]) * scale), v11 = bf16r(bf16r(sc[1][1]) * scale);
        float mx = fmaxf(fmaxf(v00, v01), fmaxf(v10, v11));
        mx = fmaxf(mx, __shfl_xor_sync(0xffffffffu, mx, 1));
        mx = fmaxf(mx, __shfl_xor_sync(0xffffffffu, mx, 2));
        float m_new = fmaxf(m_run, mx);
        float corr = exp2f((m_run - m_new) * LOG2E);
        float p00 = exp2f((v00 - m_new) * LOG2E), p01 = exp2f((v01 - m_new) * LOG2E);
        float p10 = exp2f((v10 - m_new) * LOG2E), p11 = exp2f((v11 - m_new) * LOG2E);
        l_run = l_run * corr + (p00 + p01 + p10 + p11);
        m_run = m_new;
        uint32_t pa0 = pack_bf16(p00, p01), pa2 = pack_bf16(p10, p11);
#pragma unroll
        for (int j = 0; j < 16; j++) { oacc[j][0] *= corr; oacc[j][1] *= corr; }
#pragma unroll
        for (int jj = 0; jj < 8; jj++) {
            int chunk = (jj & 3) * 2 + v_cofs;
            uint32_t addr = st + 4096 + (jj >> 2) * 2048 + v_row * 128 + ((chunk ^ (v_row & 7)) << 4);
            uint32_t r0, r1, r2, r3;
            ldsm_x4_t(addr, r0, r1, r2, r3);
            mma16816(oacc[2 * jj], pa0, 0u, pa2, 0u, r0, r1);
            mma16816(oacc[2 * jj + 1], pa0, 0u, pa2, 0u, r2, r3);
        }
        __syncwarp();
        if (lane == 0 && it + NSTAGE < NBLK) issue_stage(it + NSTAGE);
    }
    TS(4);
    l_run += __shfl_xor_sync(0xffffffffu, l_run, 1);
    l_run += __shfl_xor_sync(0xffffffffu, l_run, 2);

    CTA_SYNC();
    float* r_o = reinterpret_cast<float*>(ring);
    float* r_m = reinterpret_cast<float*>(ring + 16384);
    float* r_l = r_m + 32;
    if (lane < 16) {
        int hl = lane >> 2;
#pragma unroll
        for (int j = 0; j < 16; j++) {
            float2 v = make_float2(oacc[j][0], oacc[j][1]);
            *reinterpret_cast<float2*>(&r_o[(warp * 4 + hl) * DH + j * 8 + (lane & 3) * 2]) = v;
        }
        if ((lane & 3) == 0) { r_m[warp * 4 + hl] = m_run; r_l[warp * 4 + hl] = l_run; }
    }
    CTA_SYNC();
    {
        int hl = tid >> 6, d = (tid & 63) * 2;
        float mm = -INFINITY;
#pragma unroll
        for (int w = 0; w < NWARP; w++) mm = fmaxf(mm, r_m[w * 4 + hl]);
        float o0 = 0.f, o1 = 0.f, ll = 0.f;
#pragma unroll
        for (int w = 0; w < NWARP; w++) {
            float c = exp2f((r_m[w * 4 + hl] - mm) * LOG2E);
            float2 v = *reinterpret_cast<float2*>(&r_o[(w * 4 + hl) * DH + d]);
            o0 += c * v.x; o1 += c * v.y; ll += c * r_l[w * 4 + hl];
        }
        int pidx = (cta * 4 + hl);
        st_tag(&g_po[(size_t)pidx * DH + d], o0, epoch);
        st_tag(&g_po[(size_t)pidx * DH + d + 1], o1, epoch);
        if ((tid & 63) == 0) { st_tag(&g_pm[pidx], mm, epoch); st_tag(&g_pl[pidx], ll, epoch); }
    }
    TS(5);

    {
        int head = cta >> 2;
        int kv = head >> 2, hl = head & 3;
        {
            int bb = tid >> 7, d = tid & 127;
            int base = ((bb * 8 + kv) * NSPLIT) * 4 + hl;
            float pm[NSPLIT], pl[NSPLIT], po[NSPLIT];
            for (int tries = 0; tries < (1 << 20); tries++) {
                bool ok = true;
#pragma unroll
                for (int s = 0; s < NSPLIT; s++) {
                    unsigned long long a0 = ld_tag(&g_pm[base + s * 4]);
                    unsigned long long a1 = ld_tag(&g_pl[base + s * 4]);
                    unsigned long long a2 = ld_tag(&g_po[(size_t)(base + s * 4) * DH + d]);
                    ok = ok && ((unsigned)(a0 >> 32) == epoch) && ((unsigned)(a1 >> 32) == epoch) && ((unsigned)(a2 >> 32) == epoch);
                    pm[s] = __uint_as_float((unsigned)a0); pl[s] = __uint_as_float((unsigned)a1); po[s] = __uint_as_float((unsigned)a2);
                }
                if (ok) break;
                __nanosleep(64);
            }
            TS(6);
            float mm = -INFINITY;
#pragma unroll
            for (int s = 0; s < NSPLIT; s++) mm = fmaxf(mm, pm[s]);
            float oo = 0.f, ll = 0.f;
#pragma unroll
            for (int s = 0; s < NSPLIT; s++) {
                float c = exp2f((pm[s] - mm) * LOG2E);
                oo += c * po[s]; ll += c * pl[s];
            }
            s_vec[tid] = bf16r(oo / ll);
        }
        CTA_SYNC();
        float a[2][8];
#pragma unroll
        for (int j = 0; j < 8; j++) { a[0][j] = 0.f; a[1][j] = 0.f; }
#pragma unroll
        for (int i = 0; i < 8; i++) {
            int r = (tid >> 4) + 16 * i;
            float o0 = s_vec[r], o1 = s_vec[128 + r];
            uint32_t w[4] = {wov[i].x, wov[i].y, wov[i].z, wov[i].w};
#pragma unroll
            for (int j = 0; j < 4; j++) {
                float lo = bf_lo(w[j]), hi = bf_hi(w[j]);
                a[0][2 * j] += o0 * lo; a[0][2 * j + 1] += o0 * hi;
                a[1][2 * j] += o1 * lo; a[1][2 * j + 1] += o1 * hi;
            }
        }
#pragma unroll
        for (int j = 0; j < 8; j++) {
            a[0][j] += __shfl_xor_sync(0xffffffffu, a[0][j], 16);
            a[1][j] += __shfl_xor_sync(0xffffffffu, a[1][j], 16);
        }
        float* s_p = reinterpret_cast<float*>(ring);
        if (lane < 16) {
#pragma unroll
            for (int bb = 0; bb < 2; bb++) {
                float4* dst = reinterpret_cast<float4*>(&s_p[(warp * 2 + bb) * 128 + lane * 8]);
                dst[0] = make_float4(a[bb][0], a[bb][1], a[bb][2], a[bb][3]);
                dst[1] = make_float4(a[bb][4], a[bb][5], a[bb][6], a[bb][7]);
            }
        }
        CTA_SYNC();
        if (tid < 64) {
            int bb = tid >> 5, c4 = (tid & 31) * 4;
            float4 acc = make_float4(0.f, 0.f, 0.f, 0.f);
#pragma unroll
            for (int w = 0; w < NWARP; w++) {
                float4 v = *reinterpret_cast<float4*>(&s_p[(w * 2 + bb) * 128 + c4]);
                acc.x += v.x; acc.y += v.y; acc.z += v.z; acc.w += v.w;
            }
            red_v4(&g_attn_acc[bb * 512 + (cta & 3) * 128 + c4], acc.x, acc.y, acc.z, acc.w);
        }
    }
    TS(7);
    grid_barrier();
    TS(8);

    float h00, h01, h10, h11;
    {
        float2 aa = __ldcg(reinterpret_cast<const float2*>(&g_attn_acc[2 * tid]));
        float2 ab = __ldcg(reinterpret_cast<const float2*>(&g_attn_acc[512 + 2 * tid]));
        h00 = bf16r(bf_lo(xv0) + bf16r(aa.x)); h01 = bf16r(bf_hi(xv0) + bf16r(aa.y));
        h10 = bf16r(bf_lo(xv1) + bf16r(ab.x)); h11 = bf16r(bf_hi(xv1) + bf16r(ab.y));
        s_vec[2 * tid] = h00; s_vec[2 * tid + 1] = h01;
        s_vec[512 + 2 * tid] = h10; s_vec[512 + 2 * tid + 1] = h11;
        CTA_SYNC();
        layernorm_2x512(s_vec, s_red, tid);
        if (cta < 112) {
            float f[2][8];
#pragma unroll
            for (int j = 0; j < 8; j++) { f[0][j] = 0.f; f[1][j] = 0.f; }
#pragma unroll
            for (int i = 0; i < 4; i++) {
                int r = (tid >> 1) + 128 * i;
                float n0 = s_vec[r], n1 = s_vec[512 + r];
                uint32_t w[4] = {w1v[i].x, w1v[i].y, w1v[i].z, w1v[i].w};
#pragma unroll
                for (int j = 0; j < 4; j++) {
                    float lo = bf_lo(w[j]), hi = bf_hi(w[j]);
                    f[0][2 * j] += n0 * lo; f[0][2 * j + 1] += n0 * hi;
                    f[1][2 * j] += n1 * lo; f[1][2 * j + 1] += n1 * hi;
                }
            }
#pragma unroll
            for (int o = 2; o < 32; o <<= 1) {
#pragma unroll
                for (int j = 0; j < 8; j++) {
                    f[0][j] += __shfl_xor_sync(0xffffffffu, f[0][j], o);
                    f[1][j] += __shfl_xor_sync(0xffffffffu, f[1][j], o);
                }
            }
            float* s_fp = reinterpret_cast<float*>(ring);
            if (lane < 2) {
#pragma unroll
                for (int j = 0; j < 8; j++) {
                    s_fp[(warp * 2 + 0) * 16 + lane * 8 + j] = f[0][j];
                    s_fp[(warp * 2 + 1) * 16 + lane * 8 + j] = f[1][j];
                }
            }
            CTA_SYNC();
            if (tid < 32) {
                int bb = tid >> 4, c = tid & 15;
                float sacc = 0.f;
#pragma unroll
                for (int w = 0; w < NWARP; w++) sacc += s_fp[(w * 2 + bb) * 16 + c];
                float bias = __bfloat162float(b1[cta * 16 + c]);
                float hh = bf16r(bf16r(sacc) + bias);
                s_f[tid] = bf16r(gelu_tanh(hh));
            }
            CTA_SYNC();
            float a[2][8];
#pragma unroll
            for (int j = 0; j < 8; j++) { a[0][j] = 0.f; a[1][j] = 0.f; }
#pragma unroll
            for (int i = 0; i < 4; i++) {
                int r = (tid >> 6) + 4 * i;
                float f0 = s_f[r], f1 = s_f[16 + r];
                uint32_t w[4] = {w2v[i].x, w2v[i].y, w2v[i].z, w2v[i].w};
#pragma unroll
                for (int j = 0; j < 4; j++) {
                    float lo = bf_lo(w[j]), hi = bf_hi(w[j]);
                    a[0][2 * j] += f0 * lo; a[0][2 * j + 1] += f0 * hi;
                    a[1][2 * j] += f1 * lo; a[1][2 * j + 1] += f1 * hi;
                }
            }
            float* s_p = reinterpret_cast<float*>(ring) + 1024;
            {
                int g = tid >> 6, c8 = (tid & 63) * 8;
#pragma unroll
                for (int bb = 0; bb < 2; bb++) {
                    float4* dst = reinterpret_cast<float4*>(&s_p[(g * 2 + bb) * 512 + c8]);
                    dst[0] = make_float4(a[bb][0], a[bb][1], a[bb][2], a[bb][3]);
                    dst[1] = make_float4(a[bb][4], a[bb][5], a[bb][6], a[bb][7]);
                }
            }
            CTA_SYNC();
            {
                int bb = tid >> 7, c4 = (tid & 127) * 4;
                float4 acc = make_float4(0.f, 0.f, 0.f, 0.f);
#pragma unroll
                for (int g = 0; g < 4; g++) {
                    float4 v = *reinterpret_cast<float4*>(&s_p[(g * 2 + bb) * 512 + c4]);
                    acc.x += v.x; acc.y += v.y; acc.z += v.z; acc.w += v.w;
                }
                red_v4(&g_out_acc[(cta & 3) * 1024 + bb * 512 + c4], acc.x, acc.y, acc.z, acc.w);
            }
        }
    }
    TS(9);
    __shared__ unsigned s_last;
    CTA_SYNC();
    if (tid == 0) {
        __threadfence();
        unsigned old = atomicAdd(&g_done, 1u);
        s_last = ((old % NCTA) == NCTA - 1) ? 1u : 0u;
        __threadfence();
    }
    CTA_SYNC();
    if (s_last) {
        float2 oa = make_float2(0.f, 0.f), ob = make_float2(0.f, 0.f);
#pragma unroll
        for (int c = 0; c < 4; c++) {
            float2 va = __ldcg(reinterpret_cast<const float2*>(&g_out_acc[c * 1024 + 2 * tid]));
            float2 vb = __ldcg(reinterpret_cast<const float2*>(&g_out_acc[c * 1024 + 512 + 2 * tid]));
            oa.x += va.x; oa.y += va.y; ob.x += vb.x; ob.y += vb.y;
        }
        uint32_t bb = *reinterpret_cast<const uint32_t*>(b2 + 2 * tid);
        float bl = bf_lo(bb), bhh = bf_hi(bb);
        float r00 = h00 + bf16r(bf16r(oa.x) + bl), r01 = h01 + bf16r(bf16r(oa.y) + bhh);
        float r10 = h10 + bf16r(bf16r(ob.x) + bl), r11 = h11 + bf16r(bf16r(ob.y) + bhh);
        *reinterpret_cast<uint32_t*>(out + 2 * tid) = pack_bf16(r00, r01);
        *reinterpret_cast<uint32_t*>(out + 512 + 2 * tid) = pack_bf16(r10, r11);
        for (int i = tid; i < NB * DM; i += NTHREADS) g_attn_acc[i] = 0.f;
        for (int i = tid; i < 4 * NB * DM; i += NTHREADS) g_out_acc[i] = 0.f;
        if (tid == 0) g_epoch = epoch;
    }
    TS(10);
}

typedef CUresult (*PFN_encodeTiled)(CUtensorMap*, CUtensorMapDataType, cuuint32_t, void*, const cuuint64_t*,
                                    const cuuint64_t*, const cuuint32_t*, const cuuint32_t*, CUtensorMapInterleave,
                                    CUtensorMapSwizzle, CUtensorMapL2promotion, CUtensorMapFloatOOBfill);

}

extern "C" void kernel_launch(void* const* d_in, const int* in_sizes, int n_in, void* d_out, int out_size) {
    static PFN_encodeTiled enc = nullptr;
    if (!enc) {
        void* fn = nullptr;
        cudaDriverEntryPointQueryResult qres;
        cudaGetDriverEntryPoint("cuTensorMapEncodeTiled", &fn, cudaEnableDefault, &qres);
        enc = (PFN_encodeTiled)fn;
        cudaFuncSetAttribute(fused_kernel, cudaFuncAttributeMaxDynamicSharedMemorySize, SMEM_BYTES);
    }
    CUtensorMap mapK, mapV;
    cuuint64_t gdim[2] = {(cuuint64_t)DH, (cuuint64_t)NB * HKV * SK};
    cuuint64_t gstr[1] = {(cuuint64_t)DH * 2};
    cuuint32_t box[2] = {64, 16};
    cuuint32_t estr[2] = {1, 1};
    enc(&mapK, CU_TENSOR_MAP_DATA_TYPE_BFLOAT16, 2, d_in[1], gdim, gstr, box, estr, CU_TENSOR_MAP_INTERLEAVE_NONE,
        CU_TENSOR_MAP_SWIZZLE_128B, CU_TENSOR_MAP_L2_PROMOTION_L2_128B, CU_TENSOR_MAP_FLOAT_OOB_FILL_NONE);
    enc(&mapV, CU_TENSOR_MAP_DATA_TYPE_BFLOAT16, 2, d_in[2], gdim, gstr, box, estr, CU_TENSOR_MAP_INTERLEAVE_NONE,
        CU_TENSOR_MAP_SWIZZLE_128B, CU_TENSOR_MAP_L2_PROMOTION_L2_128B, CU_TENSOR_MAP_FLOAT_OOB_FILL_NONE);
    fused_kernel<<<NCTA, NTHREADS, SMEM_BYTES>>>(
        mapK, mapV, (const __nv_bfloat16*)d_in[0], (const __nv_bfloat16*)d_in[3], (const __nv_bfloat16*)d_in[4],
        (const __nv_bfloat16*)d_in[6], (const __nv_bfloat16*)d_in[7], (const __nv_bfloat16*)d_in[8],
        (const __nv_bfloat16*)d_in[9], (__nv_bfloat16*)d_out);
}
```

```cpp
#include <cuda_runtime.h>
#include <cuda_bf16.h>
#include <cuda.h>
#include <stdint.h>

namespace {

constexpr int NB = 2, DM = 512, HQ = 32, HKV = 8, SK = 8192, DH = 128, FF = 1792;
constexpr int NCTA = 128, NSPLIT = 8, KEYS_PER_CTA = SK / NSPLIT;
constexpr int NWARP = 8, NTHREADS = NWARP * 32;
constexpr int NSTAGE = 3;
#define REST_MODE 1
#define EARLY_W 0
#define QTRIES (1 << 20)
#define L2PF 0
#define LATE_W 0
#define PF_IT 1
#define QSLEEP 400
#define PRE_STAGES 0
constexpr int STAGE_BYTES = 8192;
constexpr int NBLK = KEYS_PER_CTA / (16 * NWARP);
constexpr int RING_BYTES = NWARP * NSTAGE * STAGE_BYTES;
constexpr int SMEM_BYTES = RING_BYTES + 4096 + 2048 + 1024;

__device__ unsigned long long g_q64[NB * HQ * DH / 2];
__device__ unsigned g_epoch;
__device__ unsigned long long g_pm[16 * NSPLIT * 4];
__device__ unsigned long long g_pl[16 * NSPLIT * 4];
__device__ unsigned long long g_po[16 * NSPLIT * 4 * DH];
__device__ float g_attn_acc[NB * DM];
__device__ float g_out_acc[4 * NB * DM];
__device__ unsigned g_bar;
__device__ unsigned g_ticket[16 * 32];
__device__ unsigned g_done;

#define TS(i)
#define CTA_SYNC() asm volatile("bar.sync 1, 256;" ::: "memory")
__device__ __forceinline__ uint32_t smem_u32(const void* p) {
    return (uint32_t)__cvta_generic_to_shared(p);
}
__device__ __forceinline__ float bf16r(float x) {
    return __bfloat162float(__float2bfloat16_rn(x));
}
__device__ __forceinline__ uint32_t pack_bf16(float lo, float hi) {
    __nv_bfloat162 v = __floats2bfloat162_rn(lo, hi);
    return *reinterpret_cast<uint32_t*>(&v);
}
__device__ __forceinline__ float bf_lo(uint32_t v) { return __uint_as_float(v << 16); }
__device__ __forceinline__ float bf_hi(uint32_t v) { return __uint_as_float(v & 0xffff0000u); }

__device__ __forceinline__ void mbar_init(uint32_t bar, uint32_t cnt) {
    asm volatile("mbarrier.init.shared::cta.b64 [%0], %1;" ::"r"(bar), "r"(cnt) : "memory");
}
__device__ __forceinline__ void mbar_expect_tx(uint32_t bar, uint32_t bytes) {
    asm volatile("mbarrier.arrive.expect_tx.shared::cta.b64 _, [%0], %1;" ::"r"(bar), "r"(bytes) : "memory");
}
__device__ __forceinline__ void mbar_wait(uint32_t bar, uint32_t parity) {
    for (int i = 0; i < (1 << 22); i++) {
        uint32_t ok;
        asm volatile(
            "{\n"
            ".reg .pred p;\n"
            "mbarrier.try_wait.parity.shared::cta.b64 p, [%1], %2;\n"
            "selp.u32 %0, 1, 0, p;\n"
            "}\n" : "=r"(ok) : "r"(bar), "r"(parity) : "memory");
        if (ok) break;
    }
}
__device__ __forceinline__ void tma_2d(uint32_t dst, const CUtensorMap* map, uint32_t bar, int c0, int c1) {
    asm volatile(
        "cp.async.bulk.tensor.2d.shared::cluster.global.mbarrier::complete_tx::bytes [%0], [%1, {%3, %4}], [%2];"
        ::"r"(dst), "l"(map), "r"(bar), "r"(c0), "r"(c1) : "memory");
}
__device__ __forceinline__ void ldsm_x4(uint32_t addr, uint32_t& r0, uint32_t& r1, uint32_t& r2, uint32_t& r3) {
    asm volatile("ldmatrix.sync.aligned.m8n8.x4.shared.b16 {%0,%1,%2,%3}, [%4];"
                 : "=r"(r0), "=r"(r1), "=r"(r2), "=r"(r3) : "r"(addr) : "memory");
}
__device__ __forceinline__ void ldsm_x4_t(uint32_t addr, uint32_t& r0, uint32_t& r1, uint32_t& r2, uint32_t& r3) {
    asm volatile("ldmatrix.sync.aligned.m8n8.x4.trans.shared.b16 {%0,%1,%2,%3}, [%4];"
                 : "=r"(r0), "=r"(r1), "=r"(r2), "=r"(r3) : "r"(addr) : "memory");
}
__device__ __forceinline__ void mma16816(float* c, uint32_t a0, uint32_t a1, uint32_t a2, uint32_t a3,
                                         uint32_t b0, uint32_t b1) {
    asm volatile(
        "mma.sync.aligned.m16n8k16.row.col.f32.bf16.bf16.f32 {%0,%1,%2,%3}, {%4,%5,%6,%7}, {%8,%9}, {%0,%1,%2,%3};"
        : "+f"(c[0]), "+f"(c[1]), "+f"(c[2]), "+f"(c[3])
        : "r"(a0), "r"(a1), "r"(a2), "r"(a3), "r"(b0), "r"(b1));
}
__device__ __forceinline__ unsigned ld_acquire(const unsigned* p) {
    unsigned v;
    asm volatile("ld.acquire.gpu.global.u32 %0, [%1];" : "=r"(v) : "l"(p) : "memory");
    return v;
}
__device__ __forceinline__ uint4 ldg_nc_v4(const void* p) {
    uint4 v;
    asm volatile("ld.global.nc.L1::no_allocate.v4.u32 {%0,%1,%2,%3}, [%4];"
                 : "=r"(v.x), "=r"(v.y), "=r"(v.z), "=r"(v.w) : "l"(p));
    return v;
}
__device__ __forceinline__ uint32_t ldg_nc_u32(const void* p) {
    uint32_t v;
    asm volatile("ld.global.nc.L1::no_allocate.u32 %0, [%1];" : "=r"(v) : "l"(p));
    return v;
}

__device__ __forceinline__ void red_v4(float* p, float a, float b, float c, float d) {
    asm volatile("red.global.add.v4.f32 [%0], {%1,%2,%3,%4};" ::"l"(p), "f"(a), "f"(b), "f"(c), "f"(d) : "memory");
}

__device__ __forceinline__ void st_tag(unsigned long long* p, float v, unsigned tag) {
    unsigned long long w = ((unsigned long long)tag << 32) | __float_as_uint(v);
    asm volatile("st.relaxed.gpu.global.u64 [%0], %1;" ::"l"(p), "l"(w) : "memory");
}
__device__ __forceinline__ unsigned long long ld_tag(const unsigned long long* p) {
    unsigned long long w;
    asm volatile("ld.relaxed.gpu.global.u64 %0, [%1];" : "=l"(w) : "l"(p) : "memory");
    return w;
}

__device__ __forceinline__ void grid_barrier() {
    CTA_SYNC();
    if (threadIdx.x == 0) {
        __threadfence();
        unsigned old = atomicAdd(&g_bar, 1u);
        unsigned target = (old / NCTA + 1u) * NCTA;
        unsigned iters = 0;
        while ((int)(ld_acquire(&g_bar) - target) < 0) {
            if (++iters > 2000000u) break;
        }
        __threadfence();
    }
    CTA_SYNC();
}

__device__ __forceinline__ void layernorm_2x512(float* v, float* red, int tid) {
    int warp = tid >> 5, lane = tid & 31;
    float a0 = v[2 * tid], a1 = v[2 * tid + 1], b0 = v[512 + 2 * tid], b1 = v[512 + 2 * tid + 1];
    float sa = a0 + a1, sb = b0 + b1;
#pragma unroll
    for (int o = 16; o > 0; o >>= 1) {
        sa += __shfl_xor_sync(0xffffffffu, sa, o);
        sb += __shfl_xor_sync(0xffffffffu, sb, o);
    }
    if (lane == 0) { red[warp] = sa; red[8 + warp] = sb; }
    CTA_SYNC();
    float ma = 0.f, mb = 0.f;
#pragma unroll
    for (int w = 0; w < 8; w++) { ma += red[w]; mb += red[8 + w]; }
    ma *= (1.f / 512.f); mb *= (1.f / 512.f);
    float da0 = a0 - ma, da1 = a1 - ma, db0 = b0 - mb, db1 = b1 - mb;
    float va = da0 * da0 + da1 * da1, vb = db0 * db0 + db1 * db1;
#pragma unroll
    for (int o = 16; o > 0; o >>= 1) {
        va += __shfl_xor_sync(0xffffffffu, va, o);
        vb += __shfl_xor_sync(0xffffffffu, vb, o);
    }
    CTA_SYNC();
    if (lane == 0) { red[16 + warp] = va; red[24 + warp] = vb; }
    CTA_SYNC();
    va = 0.f; vb = 0.f;
#pragma unroll
    for (int w = 0; w < 8; w++) { va += red[16 + w]; vb += red[24 + w]; }
    va = bf16r(va * (1.f / 512.f)); vb = bf16r(vb * (1.f / 512.f));
    float mra = bf16r(ma), mrb = bf16r(mb);
    float sda = bf16r(sqrtf(bf16r(va + 1e-5f))), sdb = bf16r(sqrtf(bf16r(vb + 1e-5f)));
    v[2 * tid] = bf16r(bf16r(a0 - mra) / sda);
    v[2 * tid + 1] = bf16r(bf16r(a1 - mra) / sda);
    v[512 + 2 * tid] = bf16r(bf16r(b0 - mrb) / sdb);
    v[512 + 2 * tid + 1] = bf16r(bf16r(b1 - mrb) / sdb);
    CTA_SYNC();
}

__device__ __forceinline__ float gelu_tanh(float x) {
    const float k0 = 0.7978845608028654f, k1 = 0.044715f;
    float inner = k0 * (x + k1 * x * x * x);
    return 0.5f * x * (1.f + tanhf(inner));
}

__global__ void __launch_bounds__(NTHREADS, 1)
fused_kernel(const __grid_constant__ CUtensorMap mapK, const __grid_constant__ CUtensorMap mapV,
             const __nv_bfloat16* __restrict__ x, const __nv_bfloat16* __restrict__ wq,
             const __nv_bfloat16* __restrict__ wo, const __nv_bfloat16* __restrict__ w1,
             const __nv_bfloat16* __restrict__ b1, const __nv_bfloat16* __restrict__ w2,
             const __nv_bfloat16* __restrict__ b2, __nv_bfloat16* __restrict__ out) {
    extern __shared__ __align__(1024) uint8_t smem_raw[];
    uint8_t* smem = smem_raw + ((1024u - (smem_u32(smem_raw) & 1023u)) & 1023u);
    uint8_t* ring = smem;
    uint64_t* bars = reinterpret_cast<uint64_t*>(smem + RING_BYTES);
    float* s_vec = reinterpret_cast<float*>(smem + RING_BYTES + 256);
    float* s_red = reinterpret_cast<float*>(smem + RING_BYTES + 256 + 4096);
    float* s_o = s_red + 64;
    float* s_f = s_o + 64;

    const int tid = threadIdx.x, warp = tid >> 5, lane = tid & 31;
    const int cta = blockIdx.x;
    const int bh = cta >> 3, split = cta & 7;
    const int b = bh >> 3, kvh = bh & 7;

    TS(0);
    const uint32_t ring_w = smem_u32(ring) + warp * (NSTAGE * STAGE_BYTES);
    const uint32_t bar_w = smem_u32(bars) + warp * (NSTAGE * 8);
    if (lane == 0) {
#pragma unroll
        for (int s = 0; s < NSTAGE; s++) mbar_init(bar_w + s * 8, 1);
        asm volatile("fence.mbarrier_init.release.cluster;" ::: "memory");
    }
    __syncwarp();
    const unsigned epoch = __ldcg(&g_epoch) + 1u;
    uint32_t xv0 = ldg_nc_u32(x + 2 * tid);
    uint32_t xv1 = ldg_nc_u32(x + 512 + 2 * tid);
    uint4 wqv[8];
    {
        const __nv_bfloat16* p = wq + (size_t)(tid >> 2) * (HQ * DH) + cta * 32 + (tid & 3) * 8;
#pragma unroll
        for (int i = 0; i < 8; i++) wqv[i] = ldg_nc_v4(p + (size_t)i * 64 * (HQ * DH));
    }
    const int row0 = bh * SK + split * KEYS_PER_CTA + warp * 16;
    auto issue_blk = [&](int s, int blk) {
        uint32_t dst = ring_w + s * STAGE_BYTES;
        uint32_t bar = bar_w + s * 8;
        int r = bh * SK + blk * 16;
        mbar_expect_tx(bar, STAGE_BYTES);
        tma_2d(dst, &mapK, bar, 0, r);
        tma_2d(dst + 2048, &mapK, bar, 64, r);
        tma_2d(dst + 4096, &mapV, bar, 0, r);
        tma_2d(dst + 6144, &mapV, bar, 64, r);
    };
    auto issue_stage = [&](int s) { issue_blk(s, s * 64 + split * 8 + warp); };
    if (lane == 0) {
#pragma unroll
        for (int s = 0; s < PRE_STAGES; s++) issue_stage(s);
    }
    uint4 wov[8];
    uint4 w1v[4];
    uint4 w2v[4];
    const __nv_bfloat16* wo_p = wo + (size_t)((cta >> 2) * 128 + (tid >> 4)) * DM + (cta & 3) * 128 + (tid & 15) * 8;
    const int fcta = cta < 112 ? cta : 0;
    const __nv_bfloat16* w1_p = w1 + (size_t)(tid >> 1) * FF + fcta * 16 + (tid & 1) * 8;
    const __nv_bfloat16* w2_p = w2 + (size_t)(fcta * 16 + (tid >> 6)) * DM + (tid & 63) * 8;

    TS(1);
    s_vec[2 * tid] = bf_lo(xv0); s_vec[2 * tid + 1] = bf_hi(xv0);
    s_vec[512 + 2 * tid] = bf_lo(xv1); s_vec[512 + 2 * tid + 1] = bf_hi(xv1);
    CTA_SYNC();
    layernorm_2x512(s_vec, s_red, tid);

    {
        float acc[2][8];
#pragma unroll
        for (int i = 0; i < 8; i++) { acc[0][i] = 0.f; acc[1][i] = 0.f; }
#pragma unroll
        for (int i = 0; i < 8; i++) {
            int r = (tid >> 2) + i * 64;
            float x0 = s_vec[r], x1 = s_vec[512 + r];
            uint32_t w[4] = {wqv[i].x, wqv[i].y, wqv[i].z, wqv[i].w};
#pragma unroll
            for (int j = 0; j < 4; j++) {
                float lo = bf_lo(w[j]), hi = bf_hi(w[j]);
                acc[0][2 * j] += x0 * lo; acc[0][2 * j + 1] += x0 * hi;
                acc[1][2 * j] += x1 * lo; acc[1][2 * j + 1] += x1 * hi;
            }
        }
        if (lane == 0) {
#pragma unroll
            for (int s = PRE_STAGES; s < NSTAGE; s++) issue_stage(s);
        }
#pragma unroll
        for (int o = 4; o < 32; o <<= 1) {
#pragma unroll
            for (int i = 0; i < 8; i++) {
                acc[0][i] += __shfl_xor_sync(0xffffffffu, acc[0][i], o);
                acc[1][i] += __shfl_xor_sync(0xffffffffu, acc[1][i], o);
            }
        }
        __shared__ float s_qpart[NWARP][2][32];
        if (lane < 4) {
#pragma unroll
            for (int i = 0; i < 8; i++) {
                s_qpart[warp][0][lane * 8 + i] = acc[0][i];
                s_qpart[warp][1][lane * 8 + i] = acc[1][i];
            }
        }
        CTA_SYNC();
        if (tid < 32) {
            int bb = tid >> 4, c = (tid & 15) * 2;
            float s0 = 0.f, s1 = 0.f;
#pragma unroll
            for (int w = 0; w < NWARP; w++) { s0 += s_qpart[w][bb][c]; s1 += s_qpart[w][bb][c + 1]; }
            unsigned long long v = ((unsigned long long)epoch << 32) | pack_bf16(s0, s1);
            asm volatile("st.relaxed.gpu.global.u64 [%0], %1;" ::"l"(&g_q64[(bb * (HQ * DH) + cta * 32 + c) >> 1]), "l"(v) : "memory");
        }
    }
    TS(2);

    uint32_t qa[8][2];
    {
        int hl = lane >> 2;
        const unsigned long long* qp = g_q64 + ((b * (HQ * DH) + (kvh * 4 + (hl & 3)) * DH + (lane & 3) * 2) >> 1);
        for (int tries = 0; tries < (1 << 20); tries++) {
            bool ok = true;
#pragma unroll
            for (int ks = 0; ks < 8; ks++) {
                unsigned long long v0, v1;
                asm volatile("ld.relaxed.gpu.global.u64 %0, [%1];" : "=l"(v0) : "l"(qp + ks * 8) : "memory");
                asm volatile("ld.relaxed.gpu.global.u64 %0, [%1];" : "=l"(v1) : "l"(qp + ks * 8 + 4) : "memory");
                ok = ok && ((unsigned)(v0 >> 32) == epoch) && ((unsigned)(v1 >> 32) == epoch);
                qa[ks][0] = hl < 4 ? (uint32_t)v0 : 0u;
                qa[ks][1] = hl < 4 ? (uint32_t)v1 : 0u;
            }
            if (__all_sync(0xffffffffu, ok)) break;
            __nanosleep(QSLEEP);
        }
    }
    TS(3);
    float oacc[16][4];
#pragma unroll
    for (int j = 0; j < 16; j++) { oacc[j][0] = 0.f; oacc[j][1] = 0.f; oacc[j][2] = 0.f; oacc[j][3] = 0.f; }
    float m_run = -INFINITY, l_run = 0.f;
    const float scale = 0.08838834764831845f;
    const float LOG2E = 1.4426950408889634f;

    const int lrow = lane & 7, lmat = lane >> 3;
    const int k_row = (lmat >> 1) * 8 + lrow;
    const int k_cofs = lmat & 1;
    const int v_row = (lmat & 1) * 8 + lrow;
    const int v_cofs = lmat >> 1;

#pragma unroll
    for (int it = 0; it < 8; it++) {
        wov[it] = ldg_nc_v4(wo_p + (size_t)it * 16 * DM);
        if (it < 4) w1v[it] = ldg_nc_v4(w1_p + (size_t)it * 128 * FF);
        else w2v[it - 4] = ldg_nc_v4(w2_p + (size_t)(it - 4) * 4 * DM);
    }
    int issued = NSTAGE;
    unsigned nt = 0;
    if (lane == 0) nt = NSTAGE * 64 + atomicAdd(&g_ticket[bh * 32], 1u);
#pragma unroll 1
    for (int it = 0; it < issued; it++) {
        const int s = it % NSTAGE;
        const uint32_t parity = (it / NSTAGE) & 1;
        const uint32_t st = ring_w + s * STAGE_BYTES;
        mbar_wait(bar_w + s * 8, parity);

        float sc[2][4];
#pragma unroll
        for (int j = 0; j < 2; j++) { sc[j][0] = 0.f; sc[j][1] = 0.f; sc[j][2] = 0.f; sc[j][3] = 0.f; }
#pragma unroll
        for (int ks = 0; ks < 8; ks++) {
            int chunk = (ks & 3) * 2 + k_cofs;
            uint32_t addr = st + (ks >> 2) * 2048 + k_row * 128 + ((chunk ^ (k_row & 7)) << 4);
            uint32_t r0, r1, r2, r3;
            ldsm_x4(addr, r0, r1, r2, r3);
            mma16816(sc[0], qa[ks][0], 0u, qa[ks][1], 0u, r0, r1);
            mma16816(sc[1], qa[ks][0], 0u, qa[ks][1], 0u, r2, r3);
        }
        float v00 = bf16r(bf16r(sc[0][0]) * scale), v01 = bf16r(bf16r(sc[0][1]) * scale);
        float v10 = bf16r(bf16r(sc[1][0]) * scale), v11 = bf16r(bf16r(sc[1][1]) * scale);
        float mx = fmaxf(fmaxf(v00, v01), fmaxf(v10, v11));
        mx = fmaxf(mx, __shfl_xor_sync(0xffffffffu, mx, 1));
        mx = fmaxf(mx, __shfl_xor_sync(0xffffffffu, mx, 2));
        float m_new = fmaxf(m_run, mx);
        float corr = exp2f((m_run - m_new) * LOG2E);
        float p00 = exp2f((v00 - m_new) * LOG2E), p01 = exp2f((v01 - m_new) * LOG2E);
        float p10 = exp2f((v10 - m_new) * LOG2E), p11 = exp2f((v11 - m_new) * LOG2E);
        l_run = l_run * corr + (p00 + p01 + p10 + p11);
        m_run = m_new;
        uint32_t pa0 = pack_bf16(p00, p01), pa2 = pack_bf16(p10, p11);
#pragma unroll
        for (int j = 0; j < 16; j++) { oacc[j][0] *= corr; oacc[j][1] *= corr; }
#pragma unroll
        for (int jj = 0; jj < 8; jj++) {
            int chunk = (jj & 3) * 2 + v_cofs;
            uint32_t addr = st + 4096 + (jj >> 2) * 2048 + v_row * 128 + ((chunk ^ (v_row & 7)) << 4);
            uint32_t r0, r1, r2, r3;
            ldsm_x4_t(addr, r0, r1, r2, r3);
            mma16816(oacc[2 * jj], pa0, 0u, pa2, 0u, r0, r1);
            mma16816(oacc[2 * jj + 1], pa0, 0u, pa2, 0u, r2, r3);
        }
        __syncwarp();
        int more = 0;
        if (lane == 0 && nt < 512u) {
            issue_blk(s, (int)nt);
            nt = NSTAGE * 64 + atomicAdd(&g_ticket[bh * 32], 1u);
            more = 1;
        }
        issued += __shfl_sync(0xffffffffu, more, 0);
    }
    TS(4);
    l_run += __shfl_xor_sync(0xffffffffu, l_run, 1);
    l_run += __shfl_xor_sync(0xffffffffu, l_run, 2);

    CTA_SYNC();
    float* r_o = reinterpret_cast<float*>(ring);
    float* r_m = reinterpret_cast<float*>(ring + 16384);
    float* r_l = r_m + 32;
    if (lane < 16) {
        int hl = lane >> 2;
#pragma unroll
        for (int j = 0; j < 16; j++) {
            float2 v = make_float2(oacc[j][0], oacc[j][1]);
            *reinterpret_cast<float2*>(&r_o[(warp * 4 + hl) * DH + j * 8 + (lane & 3) * 2]) = v;
        }
        if ((lane & 3) == 0) { r_m[warp * 4 + hl] = m_run; r_l[warp * 4 + hl] = l_run; }
    }
    CTA_SYNC();
    {
        int hl = tid >> 6, d = (tid & 63) * 2;
        float mm = -INFINITY;
#pragma unroll
        for (int w = 0; w < NWARP; w++) mm = fmaxf(mm, r_m[w * 4 + hl]);
        float o0 = 0.f, o1 = 0.f, ll = 0.f;
#pragma unroll
        for (int w = 0; w < NWARP; w++) {
            float c = exp2f((r_m[w * 4 + hl] - mm) * LOG2E);
            float2 v = *reinterpret_cast<float2*>(&r_o[(w * 4 + hl) * DH + d]);
            o0 += c * v.x; o1 += c * v.y; ll += c * r_l[w * 4 + hl];
        }
        int pidx = (cta * 4 + hl);
        st_tag(&g_po[(size_t)pidx * DH + d], o0, epoch);
        st_tag(&g_po[(size_t)pidx * DH + d + 1], o1, epoch);
        if ((tid & 63) == 0) { st_tag(&g_pm[pidx], mm, epoch); st_tag(&g_pl[pidx], ll, epoch); }
    }
    TS(5);

    {
        int head = cta >> 2;
        int kv = head >> 2, hl = head & 3;
        {
            int bb = tid >> 7, d = tid & 127;
            int base = ((bb * 8 + kv) * NSPLIT) * 4 + hl;
            float pm[NSPLIT], pl[NSPLIT], po[NSPLIT];
            for (int tries = 0; tries < (1 << 20); tries++) {
                bool ok = true;
#pragma unroll
                for (int s = 0; s < NSPLIT; s++) {
                    unsigned long long a0 = ld_tag(&g_pm[base + s * 4]);
                    unsigned long long a1 = ld_tag(&g_pl[base + s * 4]);
                    unsigned long long a2 = ld_tag(&g_po[(size_t)(base + s * 4) * DH + d]);
                    ok = ok && ((unsigned)(a0 >> 32) == epoch) && ((unsigned)(a1 >> 32) == epoch) && ((unsigned)(a2 >> 32) == epoch);
                    pm[s] = __uint_as_float((unsigned)a0); pl[s] = __uint_as_float((unsigned)a1); po[s] = __uint_as_float((unsigned)a2);
                }
                if (ok) break;
                __nanosleep(64);
            }
            TS(6);
            float mm = -INFINITY;
#pragma unroll
            for (int s = 0; s < NSPLIT; s++) mm = fmaxf(mm, pm[s]);
            float oo = 0.f, ll = 0.f;
#pragma unroll
            for (int s = 0; s < NSPLIT; s++) {
                float c = exp2f((pm[s] - mm) * LOG2E);
                oo += c * po[s]; ll += c * pl[s];
            }
            s_vec[tid] = bf16r(oo / ll);
        }
        CTA_SYNC();
        float a[2][8];
#pragma unroll
        for (int j = 0; j < 8; j++) { a[0][j] = 0.f; a[1][j] = 0.f; }
#pragma unroll
        for (int i = 0; i < 8; i++) {
            int r = (tid >> 4) + 16 * i;
            float o0 = s_vec[r], o1 = s_vec[128 + r];
            uint32_t w[4] = {wov[i].x, wov[i].y, wov[i].z, wov[i].w};
#pragma unroll
            for (int j = 0; j < 4; j++) {
                float lo = bf_lo(w[j]), hi = bf_hi(w[j]);
                a[0][2 * j] += o0 * lo; a[0][2 * j + 1] += o0 * hi;
                a[1][2 * j] += o1 * lo; a[1][2 * j + 1] += o1 * hi;
            }
        }
#pragma unroll
        for (int j = 0; j < 8; j++) {
            a[0][j] += __shfl_xor_sync(0xffffffffu, a[0][j], 16);
            a[1][j] += __shfl_xor_sync(0xffffffffu, a[1][j], 16);
        }
        float* s_p = reinterpret_cast<float*>(ring);
        if (lane < 16) {
#pragma unroll
            for (int bb = 0; bb < 2; bb++) {
                float4* dst = reinterpret_cast<float4*>(&s_p[(warp * 2 + bb) * 128 + lane * 8]);
                dst[0] = make_float4(a[bb][0], a[bb][1], a[bb][2], a[bb][3]);
                dst[1] = make_float4(a[bb][4], a[bb][5], a[bb][6], a[bb][7]);
            }
        }
        CTA_SYNC();
        if (tid < 64) {
            int bb = tid >> 5, c4 = (tid & 31) * 4;
            float4 acc = make_float4(0.f, 0.f, 0.f, 0.f);
#pragma unroll
            for (int w = 0; w < NWARP; w++) {
                float4 v = *reinterpret_cast<float4*>(&s_p[(w * 2 + bb) * 128 + c4]);
                acc.x += v.x; acc.y += v.y; acc.z += v.z; acc.w += v.w;
            }
            red_v4(&g_attn_acc[bb * 512 + (cta & 3) * 128 + c4], acc.x, acc.y, acc.z, acc.w);
        }
    }
    TS(7);
    grid_barrier();
    TS(8);

    float h00, h01, h10, h11;
    {
        float2 aa = __ldcg(reinterpret_cast<const float2*>(&g_attn_acc[2 * tid]));
        float2 ab = __ldcg(reinterpret_cast<const float2*>(&g_attn_acc[512 + 2 * tid]));
        h00 = bf16r(bf_lo(xv0) + bf16r(aa.x)); h01 = bf16r(bf_hi(xv0) + bf16r(aa.y));
        h10 = bf16r(bf_lo(xv1) + bf16r(ab.x)); h11 = bf16r(bf_hi(xv1) + bf16r(ab.y));
        s_vec[2 * tid] = h00; s_vec[2 * tid + 1] = h01;
        s_vec[512 + 2 * tid] = h10; s_vec[512 + 2 * tid + 1] = h11;
        CTA_SYNC();
        layernorm_2x512(s_vec, s_red, tid);
        if (cta < 112) {
            float f[2][8];
#pragma unroll
            for (int j = 0; j < 8; j++) { f[0][j] = 0.f; f[1][j] = 0.f; }
#pragma unroll
            for (int i = 0; i < 4; i++) {
                int r = (tid >> 1) + 128 * i;
                float n0 = s_vec[r], n1 = s_vec[512 + r];
                uint32_t w[4] = {w1v[i].x, w1v[i].y, w1v[i].z, w1v[i].w};
#pragma unroll
                for (int j = 0; j < 4; j++) {
                    float lo = bf_lo(w[j]), hi = bf_hi(w[j]);
                    f[0][2 * j] += n0 * lo; f[0][2 * j + 1] += n0 * hi;
                    f[1][2 * j] += n1 * lo; f[1][2 * j + 1] += n1 * hi;
                }
            }
#pragma unroll
            for (int o = 2; o < 32; o <<= 1) {
#pragma unroll
                for (int j = 0; j < 8; j++) {
                    f[0][j] += __shfl_xor_sync(0xffffffffu, f[0][j], o);
                    f[1][j] += __shfl_xor_sync(0xffffffffu, f[1][j], o);
                }
            }
            float* s_fp = reinterpret_cast<float*>(ring);
            if (lane < 2) {
#pragma unroll
                for (int j = 0; j < 8; j++) {
                    s_fp[(warp * 2 + 0) * 16 + lane * 8 + j] = f[0][j];
                    s_fp[(warp * 2 + 1) * 16 + lane * 8 + j] = f[1][j];
                }
            }
            CTA_SYNC();
            if (tid < 32) {
                int bb = tid >> 4, c = tid & 15;
                float sacc = 0.f;
#pragma unroll
                for (int w = 0; w < NWARP; w++) sacc += s_fp[(w * 2 + bb) * 16 + c];
                float bias = __bfloat162float(b1[cta * 16 + c]);
                float hh = bf16r(bf16r(sacc) + bias);
                s_f[tid] = bf16r(gelu_tanh(hh));
            }
            CTA_SYNC();
            float a[2][8];
#pragma unroll
            for (int j = 0; j < 8; j++) { a[0][j] = 0.f; a[1][j] = 0.f; }
#pragma unroll
            for (int i = 0; i < 4; i++) {
                int r = (tid >> 6) + 4 * i;
                float f0 = s_f[r], f1 = s_f[16 + r];
                uint32_t w[4] = {w2v[i].x, w2v[i].y, w2v[i].z, w2v[i].w};
#pragma unroll
                for (int j = 0; j < 4; j++) {
                    float lo = bf_lo(w[j]), hi = bf_hi(w[j]);
                    a[0][2 * j] += f0 * lo; a[0][2 * j + 1] += f0 * hi;
                    a[1][2 * j] += f1 * lo; a[1][2 * j + 1] += f1 * hi;
                }
            }
            float* s_p = reinterpret_cast<float*>(ring) + 1024;
            {
                int g = tid >> 6, c8 = (tid & 63) * 8;
#pragma unroll
                for (int bb = 0; bb < 2; bb++) {
                    float4* dst = reinterpret_cast<float4*>(&s_p[(g * 2 + bb) * 512 + c8]);
                    dst[0] = make_float4(a[bb][0], a[bb][1], a[bb][2], a[bb][3]);
                    dst[1] = make_float4(a[bb][4], a[bb][5], a[bb][6], a[bb][7]);
                }
            }
            CTA_SYNC();
            {
                int bb = tid >> 7, c4 = (tid & 127) * 4;
                float4 acc = make_float4(0.f, 0.f, 0.f, 0.f);
#pragma unroll
                for (int g = 0; g < 4; g++) {
                    float4 v = *reinterpret_cast<float4*>(&s_p[(g * 2 + bb) * 512 + c4]);
                    acc.x += v.x; acc.y += v.y; acc.z += v.z; acc.w += v.w;
                }
                red_v4(&g_out_acc[(cta & 3) * 1024 + bb * 512 + c4], acc.x, acc.y, acc.z, acc.w);
            }
        }
    }
    TS(9);
    __shared__ unsigned s_last;
    CTA_SYNC();
    if (tid == 0) {
        __threadfence();
        unsigned old = atomicAdd(&g_done, 1u);
        s_last = ((old % NCTA) == NCTA - 1) ? 1u : 0u;
        __threadfence();
    }
    CTA_SYNC();
    if (s_last) {
        float2 oa = make_float2(0.f, 0.f), ob = make_float2(0.f, 0.f);
#pragma unroll
        for (int c = 0; c < 4; c++) {
            float2 va = __ldcg(reinterpret_cast<const float2*>(&g_out_acc[c * 1024 + 2 * tid]));
            float2 vb = __ldcg(reinterpret_cast<const float2*>(&g_out_acc[c * 1024 + 512 + 2 * tid]));
            oa.x += va.x; oa.y += va.y; ob.x += vb.x; ob.y += vb.y;
        }
        uint32_t bb = *reinterpret_cast<const uint32_t*>(b2 + 2 * tid);
        float bl = bf_lo(bb), bhh = bf_hi(bb);
        float r00 = h00 + bf16r(bf16r(oa.x) + bl), r01 = h01 + bf16r(bf16r(oa.y) + bhh);
        float r10 = h10 + bf16r(bf16r(ob.x) + bl), r11 = h11 + bf16r(bf16r(ob.y) + bhh);
        *reinterpret_cast<uint32_t*>(out + 2 * tid) = pack_bf16(r00, r01);
        *reinterpret_cast<uint32_t*>(out + 512 + 2 * tid) = pack_bf16(r10, r11);
        for (int i = tid; i < NB * DM; i += NTHREADS) g_attn_acc[i] = 0.f;
        for (int i = tid; i < 4 * NB * DM; i += NTHREADS) g_out_acc[i] = 0.f;
        if (tid == 0) g_epoch = epoch;
        if (tid < 16) g_ticket[tid * 32] = 0u;
    }
    TS(10);
}

typedef CUresult (*PFN_encodeTiled)(CUtensorMap*, CUtensorMapDataType, cuuint32_t, void*, const cuuint64_t*,
                                    const cuuint64_t*, const cuuint32_t*, const cuuint32_t*, CUtensorMapInterleave,
                                    CUtensorMapSwizzle, CUtensorMapL2promotion, CUtensorMapFloatOOBfill);

}

extern "C" void kernel_launch(void* const* d_in, const int* in_sizes, int n_in, void* d_out, int out_size) {
    static PFN_encodeTiled enc = nullptr;
    if (!enc) {
        void* fn = nullptr;
        cudaDriverEntryPointQueryResult qres;
        cudaGetDriverEntryPoint("cuTensorMapEncodeTiled", &fn, cudaEnableDefault, &qres);
        enc = (PFN_encodeTiled)fn;
        cudaFuncSetAttribute(fused_kernel, cudaFuncAttributeMaxDynamicSharedMemorySize, SMEM_BYTES);
    }
    CUtensorMap mapK, mapV;
    cuuint64_t gdim[2] = {(cuuint64_t)DH, (cuuint64_t)NB * HKV * SK};
    cuuint64_t gstr[1] = {(cuuint64_t)DH * 2};
    cuuint32_t box[2] = {64, 16};
    cuuint32_t estr[2] = {1, 1};
    enc(&mapK, CU_TENSOR_MAP_DATA_TYPE_BFLOAT16, 2, d_in[1], gdim, gstr, box, estr, CU_TENSOR_MAP_INTERLEAVE_NONE,
        CU_TENSOR_MAP_SWIZZLE_128B, CU_TENSOR_MAP_L2_PROMOTION_L2_128B, CU_TENSOR_MAP_FLOAT_OOB_FILL_NONE);
    enc(&mapV, CU_TENSOR_MAP_DATA_TYPE_BFLOAT16, 2, d_in[2], gdim, gstr, box, estr, CU_TENSOR_MAP_INTERLEAVE_NONE,
        CU_TENSOR_MAP_SWIZZLE_128B, CU_TENSOR_MAP_L2_PROMOTION_L2_128B, CU_TENSOR_MAP_FLOAT_OOB_FILL_NONE);
    fused_kernel<<<NCTA, NTHREADS, SMEM_BYTES>>>(
        mapK, mapV, (const __nv_bfloat16*)d_in[0], (const __nv_bfloat16*)d_in[3], (const __nv_bfloat16*)d_in[4],
        (const __nv_bfloat16*)d_in[6], (const __nv_bfloat16*)d_in[7], (const __nv_bfloat16*)d_in[8],
        (const __nv_bfloat16*)d_in[9], (__nv_bfloat16*)d_out);
}
```

```cpp
#include <cuda_runtime.h>
#include <cuda_bf16.h>
#include <cuda.h>
#include <stdint.h>

namespace {

constexpr int NB = 2, DM = 512, HQ = 32, HKV = 8, SK = 8192, DH = 128, FF = 1792;
constexpr int NCTA = 128, NSPLIT = 8, KEYS_PER_CTA = SK / NSPLIT;
constexpr int NWARP = 8, NTHREADS = NWARP * 32;
constexpr int NSTAGE = 3;
#define REST_MODE 1
#define EARLY_W 0
#define QTRIES (1 << 20)
#define L2PF 0
#define LATE_W 0
#define PF_IT 1
#define QSLEEP 400
#define PRE_STAGES 0
constexpr int STAGE_BYTES = 8192;
constexpr int NBLK = KEYS_PER_CTA / (16 * NWARP);
constexpr int RING_BYTES = NWARP * NSTAGE * STAGE_BYTES;
constexpr int SMEM_BYTES = RING_BYTES + 4096 + 2048 + 1024;

__device__ unsigned long long g_q64[NB * HQ * DH / 2];
__device__ unsigned g_epoch;
__device__ unsigned long long g_pm[16 * NSPLIT * 4];
__device__ unsigned long long g_pl[16 * NSPLIT * 4];
__device__ unsigned long long g_po[16 * NSPLIT * 4 * DH];
__device__ float g_attn_acc[NB * DM];
__device__ float g_out_acc[4 * NB * DM];
__device__ unsigned g_bar;
__device__ unsigned g_done;

#define TS(i)
#define CTA_SYNC() asm volatile("bar.sync 1, 256;" ::: "memory")
__device__ __forceinline__ uint32_t smem_u32(const void* p) {
    return (uint32_t)__cvta_generic_to_shared(p);
}
__device__ __forceinline__ float bf16r(float x) {
    return __bfloat162float(__float2bfloat16_rn(x));
}
__device__ __forceinline__ uint32_t pack_bf16(float lo, float hi) {
    __nv_bfloat162 v = __floats2bfloat162_rn(lo, hi);
    return *reinterpret_cast<uint32_t*>(&v);
}
__device__ __forceinline__ float bf_lo(uint32_t v) { return __uint_as_float(v << 16); }
__device__ __forceinline__ float bf_hi(uint32_t v) { return __uint_as_float(v & 0xffff0000u); }

__device__ __forceinline__ void mbar_init(uint32_t bar, uint32_t cnt) {
    asm volatile("mbarrier.init.shared::cta.b64 [%0], %1;" ::"r"(bar), "r"(cnt) : "memory");
}
__device__ __forceinline__ void mbar_expect_tx(uint32_t bar, uint32_t bytes) {
    asm volatile("mbarrier.arrive.expect_tx.shared::cta.b64 _, [%0], %1;" ::"r"(bar), "r"(bytes) : "memory");
}
__device__ __forceinline__ void mbar_wait(uint32_t bar, uint32_t parity) {
    for (int i = 0; i < (1 << 22); i++) {
        uint32_t ok;
        asm volatile(
            "{\n"
            ".reg .pred p;\n"
            "mbarrier.try_wait.parity.shared::cta.b64 p, [%1], %2;\n"
            "selp.u32 %0, 1, 0, p;\n"
            "}\n" : "=r"(ok) : "r"(bar), "r"(parity) : "memory");
        if (ok) break;
    }
}
__device__ __forceinline__ void tma_2d(uint32_t dst, const CUtensorMap* map, uint32_t bar, int c0, int c1) {
    asm volatile(
        "cp.async.bulk.tensor.2d.shared::cluster.global.mbarrier::complete_tx::bytes [%0], [%1, {%3, %4}], [%2];"
        ::"r"(dst), "l"(map), "r"(bar), "r"(c0), "r"(c1) : "memory");
}
__device__ __forceinline__ void ldsm_x4(uint32_t addr, uint32_t& r0, uint32_t& r1, uint32_t& r2, uint32_t& r3) {
    asm volatile("ldmatrix.sync.aligned.m8n8.x4.shared.b16 {%0,%1,%2,%3}, [%4];"
                 : "=r"(r0), "=r"(r1), "=r"(r2), "=r"(r3) : "r"(addr) : "memory");
}
__device__ __forceinline__ void ldsm_x4_t(uint32_t addr, uint32_t& r0, uint32_t& r1, uint32_t& r2, uint32_t& r3) {
    asm volatile("ldmatrix.sync.aligned.m8n8.x4.trans.shared.b16 {%0,%1,%2,%3}, [%4];"
                 : "=r"(r0), "=r"(r1), "=r"(r2), "=r"(r3) : "r"(addr) : "memory");
}
__device__ __forceinline__ void mma16816(float* c, uint32_t a0, uint32_t a1, uint32_t a2, uint32_t a3,
                                         uint32_t b0, uint32_t b1) {
    asm volatile(
        "mma.sync.aligned.m16n8k16.row.col.f32.bf16.bf16.f32 {%0,%1,%2,%3}, {%4,%5,%6,%7}, {%8,%9}, {%0,%1,%2,%3};"
        : "+f"(c[0]), "+f"(c[1]), "+f"(c[2]), "+f"(c[3])
        : "r"(a0), "r"(a1), "r"(a2), "r"(a3), "r"(b0), "r"(b1));
}
__device__ __forceinline__ unsigned ld_acquire(const unsigned* p) {
    unsigned v;
    asm volatile("ld.acquire.gpu.global.u32 %0, [%1];" : "=r"(v) : "l"(p) : "memory");
    return v;
}
__device__ __forceinline__ uint4 ldg_nc_v4(const void* p) {
    uint4 v;
    asm volatile("ld.global.nc.L1::no_allocate.v4.u32 {%0,%1,%2,%3}, [%4];"
                 : "=r"(v.x), "=r"(v.y), "=r"(v.z), "=r"(v.w) : "l"(p));
    return v;
}
__device__ __forceinline__ uint32_t ldg_nc_u32(const void* p) {
    uint32_t v;
    asm volatile("ld.global.nc.L1::no_allocate.u32 %0, [%1];" : "=r"(v) : "l"(p));
    return v;
}

__device__ __forceinline__ void red_v4(float* p, float a, float b, float c, float d) {
    asm volatile("red.global.add.v4.f32 [%0], {%1,%2,%3,%4};" ::"l"(p), "f"(a), "f"(b), "f"(c), "f"(d) : "memory");
}

__device__ __forceinline__ void st_tag(unsigned long long* p, float v, unsigned tag) {
    unsigned long long w = ((unsigned long long)tag << 32) | __float_as_uint(v);
    asm volatile("st.relaxed.gpu.global.u64 [%0], %1;" ::"l"(p), "l"(w) : "memory");
}
__device__ __forceinline__ unsigned long long ld_tag(const unsigned long long* p) {
    unsigned long long w;
    asm volatile("ld.relaxed.gpu.global.u64 %0, [%1];" : "=l"(w) : "l"(p) : "memory");
    return w;
}

__device__ __forceinline__ void grid_barrier() {
    CTA_SYNC();
    if (threadIdx.x == 0) {
        __threadfence();
        unsigned old = atomicAdd(&g_bar, 1u);
        unsigned target = (old / NCTA + 1u) * NCTA;
        unsigned iters = 0;
        while ((int)(ld_acquire(&g_bar) - target) < 0) {
            if (++iters > 2000000u) break;
        }
        __threadfence();
    }
    CTA_SYNC();
}

__device__ __forceinline__ void layernorm_2x512(float* v, float* red, int tid) {
    int warp = tid >> 5, lane = tid & 31;
    float a0 = v[2 * tid], a1 = v[2 * tid + 1], b0 = v[512 + 2 * tid], b1 = v[512 + 2 * tid + 1];
    float sa = a0 + a1, sb = b0 + b1;
#pragma unroll
    for (int o = 16; o > 0; o >>= 1) {
        sa += __shfl_xor_sync(0xffffffffu, sa, o);
        sb += __shfl_xor_sync(0xffffffffu, sb, o);
    }
    if (lane == 0) { red[warp] = sa; red[8 + warp] = sb; }
    CTA_SYNC();
    float ma = 0.f, mb = 0.f;
#pragma unroll
    for (int w = 0; w < 8; w++) { ma += red[w]; mb += red[8 + w]; }
    ma *= (1.f / 512.f); mb *= (1.f / 512.f);
    float da0 = a0 - ma, da1 = a1 - ma, db0 = b0 - mb, db1 = b1 - mb;
    float va = da0 * da0 + da1 * da1, vb = db0 * db0 + db1 * db1;
#pragma unroll
    for (int o = 16; o > 0; o >>= 1) {
        va += __shfl_xor_sync(0xffffffffu, va, o);
        vb += __shfl_xor_sync(0xffffffffu, vb, o);
    }
    CTA_SYNC();
    if (lane == 0) { red[16 + warp] = va; red[24 + warp] = vb; }
    CTA_SYNC();
    va = 0.f; vb = 0.f;
#pragma unroll
    for (int w = 0; w < 8; w++) { va += red[16 + w]; vb += red[24 + w]; }
    va = bf16r(va * (1.f / 512.f)); vb = bf16r(vb * (1.f / 512.f));
    float mra = bf16r(ma), mrb = bf16r(mb);
    float sda = bf16r(sqrtf(bf16r(va + 1e-5f))), sdb = bf16r(sqrtf(bf16r(vb + 1e-5f)));
    v[2 * tid] = bf16r(bf16r(a0 - mra) / sda);
    v[2 * tid + 1] = bf16r(bf16r(a1 - mra) / sda);
    v[512 + 2 * tid] = bf16r(bf16r(b0 - mrb) / sdb);
    v[512 + 2 * tid + 1] = bf16r(bf16r(b1 - mrb) / sdb);
    CTA_SYNC();
}

__device__ __forceinline__ float gelu_tanh(float x) {
    const float k0 = 0.7978845608028654f, k1 = 0.044715f;
    float inner = k0 * (x + k1 * x * x * x);
    return 0.5f * x * (1.f + tanhf(inner));
}

__global__ void __launch_bounds__(NTHREADS, 1)
fused_kernel(const __grid_constant__ CUtensorMap mapK, const __grid_constant__ CUtensorMap mapV,
             const __nv_bfloat16* __restrict__ x, const __nv_bfloat16* __restrict__ wq,
             const __nv_bfloat16* __restrict__ wo, const __nv_bfloat16* __restrict__ w1,
             const __nv_bfloat16* __restrict__ b1, const __nv_bfloat16* __restrict__ w2,
             const __nv_bfloat16* __restrict__ b2, __nv_bfloat16* __restrict__ out) {
    extern __shared__ __align__(1024) uint8_t smem_raw[];
    uint8_t* smem = smem_raw + ((1024u - (smem_u32(smem_raw) & 1023u)) & 1023u);
    uint8_t* ring = smem;
    uint64_t* bars = reinterpret_cast<uint64_t*>(smem + RING_BYTES);
    float* s_vec = reinterpret_cast<float*>(smem + RING_BYTES + 256);
    float* s_red = reinterpret_cast<float*>(smem + RING_BYTES + 256 + 4096);
    float* s_o = s_red + 64;
    float* s_f = s_o + 64;

    const int tid = threadIdx.x, warp = tid >> 5, lane = tid & 31;
    const int cta = blockIdx.x;
    const int bh = cta >> 3, split = cta & 7;
    const int b = bh >> 3, kvh = bh & 7;

    TS(0);
    const uint32_t ring_w = smem_u32(ring) + warp * (NSTAGE * STAGE_BYTES);
    const uint32_t bar_w = smem_u32(bars) + warp * (NSTAGE * 8);
    if (lane == 0) {
#pragma unroll
        for (int s = 0; s < NSTAGE; s++) mbar_init(bar_w + s * 8, 1);
        asm volatile("fence.mbarrier_init.release.cluster;" ::: "memory");
    }
    __syncwarp();
    const unsigned epoch = __ldcg(&g_epoch) + 1u;
    uint32_t xv0 = ldg_nc_u32(x + 2 * tid);
    uint32_t xv1 = ldg_nc_u32(x + 512 + 2 * tid);
    uint4 wqv[8];
    {
        const __nv_bfloat16* p = wq + (size_t)(tid >> 2) * (HQ * DH) + cta * 32 + (tid & 3) * 8;
#pragma unroll
        for (int i = 0; i < 8; i++) wqv[i] = ldg_nc_v4(p + (size_t)i * 64 * (HQ * DH));
    }
    const int row0 = bh * SK + split * KEYS_PER_CTA + warp * 16;
    auto issue_stage = [&](int blk) {
        const int s = blk % NSTAGE;
        uint32_t dst = ring_w + s * STAGE_BYTES;
        uint32_t bar = bar_w + s * 8;
        int r = row0 + blk * 128;
        mbar_expect_tx(bar, STAGE_BYTES);
        tma_2d(dst, &mapK, bar, 0, r);
        tma_2d(dst + 2048, &mapK, bar, 64, r);
        tma_2d(dst + 4096, &mapV, bar, 0, r);
        tma_2d(dst + 6144, &mapV, bar, 64, r);
    };
    if (lane == 0) {
#pragma unroll
        for (int s = 0; s < PRE_STAGES; s++) issue_stage(s);
    }
    uint4 wov[8];
    uint4 w1v[4];
    uint4 w2v[4];
    const __nv_bfloat16* wo_p = wo + (size_t)((cta >> 2) * 128 + (tid >> 4)) * DM + (cta & 3) * 128 + (tid & 15) * 8;
    const int fcta = cta < 112 ? cta : 0;
    const __nv_bfloat16* w1_p = w1 + (size_t)(tid >> 1) * FF + fcta * 16 + (tid & 1) * 8;
    const float bias1 = __bfloat162float(b1[fcta * 16 + (tid & 15)]);
    const uint32_t bias2 = *reinterpret_cast<const uint32_t*>(b2 + 2 * tid);
    const __nv_bfloat16* w2_p = w2 + (size_t)(fcta * 16 + (tid >> 6)) * DM + (tid & 63) * 8;

    TS(1);
    s_vec[2 * tid] = bf_lo(xv0); s_vec[2 * tid + 1] = bf_hi(xv0);
    s_vec[512 + 2 * tid] = bf_lo(xv1); s_vec[512 + 2 * tid + 1] = bf_hi(xv1);
    CTA_SYNC();
    layernorm_2x512(s_vec, s_red, tid);

    {
        float acc[2][8];
#pragma unroll
        for (int i = 0; i < 8; i++) { acc[0][i] = 0.f; acc[1][i] = 0.f; }
#pragma unroll
        for (int i = 0; i < 8; i++) {
            int r = (tid >> 2) + i * 64;
            float x0 = s_vec[r], x1 = s_vec[512 + r];
            uint32_t w[4] = {wqv[i].x, wqv[i].y, wqv[i].z, wqv[i].w};
#pragma unroll
            for (int j = 0; j < 4; j++) {
                float lo = bf_lo(w[j]), hi = bf_hi(w[j]);
                acc[0][2 * j] += x0 * lo; acc[0][2 * j + 1] += x0 * hi;
                acc[1][2 * j] += x1 * lo; acc[1][2 * j + 1] += x1 * hi;
            }
        }
        if (lane == 0) {
#pragma unroll
            for (int s = PRE_STAGES; s < NSTAGE; s++) issue_stage(s);
        }
#pragma unroll
        for (int o = 4; o < 32; o <<= 1) {
#pragma unroll
            for (int i = 0; i < 8; i++) {
                acc[0][i] += __shfl_xor_sync(0xffffffffu, acc[0][i], o);
                acc[1][i] += __shfl_xor_sync(0xffffffffu, acc[1][i], o);
            }
        }
        __shared__ float s_qpart[NWARP][2][32];
        if (lane < 4) {
#pragma unroll
            for (int i = 0; i < 8; i++) {
                s_qpart[warp][0][lane * 8 + i] = acc[0][i];
                s_qpart[warp][1][lane * 8 + i] = acc[1][i];
            }
        }
        CTA_SYNC();
        if (tid < 32) {
            int bb = tid >> 4, c = (tid & 15) * 2;
            float s0 = 0.f, s1 = 0.f;
#pragma unroll
            for (int w = 0; w < NWARP; w++) { s0 += s_qpart[w][bb][c]; s1 += s_qpart[w][bb][c + 1]; }
            unsigned long long v = ((unsigned long long)epoch << 32) | pack_bf16(s0, s1);
            asm volatile("st.relaxed.gpu.global.u64 [%0], %1;" ::"l"(&g_q64[(bb * (HQ * DH) + cta * 32 + c) >> 1]), "l"(v) : "memory");
        }
    }
    TS(2);

    uint32_t qa[8][2];
    {
        int hl = lane >> 2;
        const unsigned long long* qp = g_q64 + ((b * (HQ * DH) + (kvh * 4 + (hl & 3)) * DH + (lane & 3) * 2) >> 1);
        for (int tries = 0; tries < (1 << 20); tries++) {
            bool ok = true;
#pragma unroll
            for (int ks = 0; ks < 8; ks++) {
                unsigned long long v0, v1;
                asm volatile("ld.relaxed.gpu.global.u64 %0, [%1];" : "=l"(v0) : "l"(qp + ks * 8) : "memory");
                asm volatile("ld.relaxed.gpu.global.u64 %0, [%1];" : "=l"(v1) : "l"(qp + ks * 8 + 4) : "memory");
                ok = ok && ((unsigned)(v0 >> 32) == epoch) && ((unsigned)(v1 >> 32) == epoch);
                qa[ks][0] = hl < 4 ? (uint32_t)v0 : 0u;
                qa[ks][1] = hl < 4 ? (uint32_t)v1 : 0u;
            }
            if (__all_sync(0xffffffffu, ok)) break;
            __nanosleep(QSLEEP);
        }
    }
    TS(3);
    float oacc[16][4];
#pragma unroll
    for (int j = 0; j < 16; j++) { oacc[j][0] = 0.f; oacc[j][1] = 0.f; oacc[j][2] = 0.f; oacc[j][3] = 0.f; }
    float m_run = -INFINITY, l_run = 0.f;
    const float scale = 0.08838834764831845f;
    const float LOG2E = 1.4426950408889634f;

    const int lrow = lane & 7, lmat = lane >> 3;
    const int k_row = (lmat >> 1) * 8 + lrow;
    const int k_cofs = lmat & 1;
    const int v_row = (lmat & 1) * 8 + lrow;
    const int v_cofs = lmat >> 1;

#pragma unroll
    for (int it = 0; it < NBLK; it++) {
        wov[it] = ldg_nc_v4(wo_p + (size_t)it * 16 * DM);
        if (it < 4) w1v[it] = ldg_nc_v4(w1_p + (size_t)it * 128 * FF);
        else w2v[it - 4] = ldg_nc_v4(w2_p + (size_t)(it - 4) * 4 * DM);
        const int s = it % NSTAGE;
        const uint32_t parity = (it / NSTAGE) & 1;
        const uint32_t st = ring_w + s * STAGE_BYTES;
        mbar_wait(bar_w + s * 8, parity);

        float sc[2][4];
#pragma unroll
        for (int j = 0; j < 2; j++) { sc[j][0] = 0.f; sc[j][1] = 0.f; sc[j][2] = 0.f; sc[j][3] = 0.f; }
#pragma unroll
        for (int ks = 0; ks < 8; ks++) {
            int chunk = (ks & 3) * 2 + k_cofs;
            uint32_t addr = st + (ks >> 2) * 2048 + k_row * 128 + ((chunk ^ (k_row & 7)) << 4);
            uint32_t r0, r1, r2, r3;
            ldsm_x4(addr, r0, r1, r2, r3);
            mma16816(sc[0], qa[ks][0], 0u, qa[ks][1], 0u, r0, r1);
            mma16816(sc[1], qa[ks][0], 0u, qa[ks][1], 0u, r2, r3);
        }
        float v00 = bf16r(bf16r(sc[0][0]) * scale), v01 = bf16r(bf16r(sc[0][1]) * scale);
        float v10 = bf16r(bf16r(sc[1][0]) * scale), v11 = bf16r(bf16r(sc[1][1]) * scale);
        float mx = fmaxf(fmaxf(v00, v01), fmaxf(v10, v11));
        mx = fmaxf(mx, __shfl_xor_sync(0xffffffffu, mx, 1));
        mx = fmaxf(mx, __shfl_xor_sync(0xffffffffu, mx, 2));
        float m_new = fmaxf(m_run, mx);
        float corr = exp2f((m_run - m_new) * LOG2E);
        float p00 = exp2f((v00 - m_new) * LOG2E), p01 = exp2f((v01 - m_new) * LOG2E);
        float p10 = exp2f((v10 - m_new) * LOG2E), p11 = exp2f((v11 - m_new) * LOG2E);
        l_run = l_run * corr + (p00 + p01 + p10 + p11);
        m_run = m_new;
        uint32_t pa0 = pack_bf16(p00, p01), pa2 = pack_bf16(p10, p11);
#pragma unroll
        for (int j = 0; j < 16; j++) { oacc[j][0] *= corr; oacc[j][1] *= corr; }
#pragma unroll
        for (int jj = 0; jj < 8; jj++) {
            int chunk = (jj & 3) * 2 + v_cofs;
            uint32_t addr = st + 4096 + (jj >> 2) * 2048 + v_row * 128 + ((chunk ^ (v_row & 7)) << 4);
            uint32_t r0, r1, r2, r3;
            ldsm_x4_t(addr, r0, r1, r2, r3);
            mma16816(oacc[2 * jj], pa0, 0u, pa2, 0u, r0, r1);
            mma16816(oacc[2 * jj + 1], pa0, 0u, pa2, 0u, r2, r3);
        }
        __syncwarp();
        if (lane == 0 && it + NSTAGE < NBLK) issue_stage(it + NSTAGE);
    }
    TS(4);
    l_run += __shfl_xor_sync(0xffffffffu, l_run, 1);
    l_run += __shfl_xor_sync(0xffffffffu, l_run, 2);

    CTA_SYNC();
    float* r_o = reinterpret_cast<float*>(ring);
    float* r_m = reinterpret_cast<float*>(ring + 16384);
    float* r_l = r_m + 32;
    if (lane < 16) {
        int hl = lane >> 2;
#pragma unroll
        for (int j = 0; j < 16; j++) {
            float2 v = make_float2(oacc[j][0], oacc[j][1]);
            *reinterpret_cast<float2*>(&r_o[(warp * 4 + hl) * DH + j * 8 + (lane & 3) * 2]) = v;
        }
        if ((lane & 3) == 0) { r_m[warp * 4 + hl] = m_run; r_l[warp * 4 + hl] = l_run; }
    }
    CTA_SYNC();
    {
        int hl = tid >> 6, d = (tid & 63) * 2;
        float mm = -INFINITY;
#pragma unroll
        for (int w = 0; w < NWARP; w++) mm = fmaxf(mm, r_m[w * 4 + hl]);
        float o0 = 0.f, o1 = 0.f, ll = 0.f;
#pragma unroll
        for (int w = 0; w < NWARP; w++) {
            float c = exp2f((r_m[w * 4 + hl] - mm) * LOG2E);
            float2 v = *reinterpret_cast<float2*>(&r_o[(w * 4 + hl) * DH + d]);
            o0 += c * v.x; o1 += c * v.y; ll += c * r_l[w * 4 + hl];
        }
        int pidx = (cta * 4 + hl);
        st_tag(&g_po[(size_t)pidx * DH + d], o0, epoch);
        st_tag(&g_po[(size_t)pidx * DH + d + 1], o1, epoch);
        if ((tid & 63) == 0) { st_tag(&g_pm[pidx], mm, epoch); st_tag(&g_pl[pidx], ll, epoch); }
    }
    TS(5);

    {
        int head = cta >> 2;
        int kv = head >> 2, hl = head & 3;
        {
            int bb = tid >> 7, d = tid & 127;
            int base = ((bb * 8 + kv) * NSPLIT) * 4 + hl;
            float pm[NSPLIT], pl[NSPLIT], po[NSPLIT];
            for (int tries = 0; tries < (1 << 20); tries++) {
                bool ok = true;
#pragma unroll
                for (int s = 0; s < NSPLIT; s++) {
                    unsigned long long a0 = ld_tag(&g_pm[base + s * 4]);
                    unsigned long long a1 = ld_tag(&g_pl[base + s * 4]);
                    unsigned long long a2 = ld_tag(&g_po[(size_t)(base + s * 4) * DH + d]);
                    ok = ok && ((unsigned)(a0 >> 32) == epoch) && ((unsigned)(a1 >> 32) == epoch) && ((unsigned)(a2 >> 32) == epoch);
                    pm[s] = __uint_as_float((unsigned)a0); pl[s] = __uint_as_float((unsigned)a1); po[s] = __uint_as_float((unsigned)a2);
                }
                if (ok) break;
                __nanosleep(64);
            }
            TS(6);
            float mm = -INFINITY;
#pragma unroll
            for (int s = 0; s < NSPLIT; s++) mm = fmaxf(mm, pm[s]);
            float oo = 0.f, ll = 0.f;
#pragma unroll
            for (int s = 0; s < NSPLIT; s++) {
                float c = exp2f((pm[s] - mm) * LOG2E);
                oo += c * po[s]; ll += c * pl[s];
            }
            s_vec[tid] = bf16r(oo / ll);
        }
        CTA_SYNC();
        float a[2][8];
#pragma unroll
        for (int j = 0; j < 8; j++) { a[0][j] = 0.f; a[1][j] = 0.f; }
#pragma unroll
        for (int i = 0; i < 8; i++) {
            int r = (tid >> 4) + 16 * i;
            float o0 = s_vec[r], o1 = s_vec[128 + r];
            uint32_t w[4] = {wov[i].x, wov[i].y, wov[i].z, wov[i].w};
#pragma unroll
            for (int j = 0; j < 4; j++) {
                float lo = bf_lo(w[j]), hi = bf_hi(w[j]);
                a[0][2 * j] += o0 * lo; a[0][2 * j + 1] += o0 * hi;
                a[1][2 * j] += o1 * lo; a[1][2 * j + 1] += o1 * hi;
            }
        }
#pragma unroll
        for (int j = 0; j < 8; j++) {
            a[0][j] += __shfl_xor_sync(0xffffffffu, a[0][j], 16);
            a[1][j] += __shfl_xor_sync(0xffffffffu, a[1][j], 16);
        }
        float* s_p = reinterpret_cast<float*>(ring);
        if (lane < 16) {
#pragma unroll
            for (int bb = 0; bb < 2; bb++) {
                float4* dst = reinterpret_cast<float4*>(&s_p[(warp * 2 + bb) * 128 + lane * 8]);
                dst[0] = make_float4(a[bb][0], a[bb][1], a[bb][2], a[bb][3]);
                dst[1] = make_float4(a[bb][4], a[bb][5], a[bb][6], a[bb][7]);
            }
        }
        CTA_SYNC();
        if (tid < 64) {
            int bb = tid >> 5, c4 = (tid & 31) * 4;
            float4 acc = make_float4(0.f, 0.f, 0.f, 0.f);
#pragma unroll
            for (int w = 0; w < NWARP; w++) {
                float4 v = *reinterpret_cast<float4*>(&s_p[(w * 2 + bb) * 128 + c4]);
                acc.x += v.x; acc.y += v.y; acc.z += v.z; acc.w += v.w;
            }
            red_v4(&g_attn_acc[bb * 512 + (cta & 3) * 128 + c4], acc.x, acc.y, acc.z, acc.w);
        }
    }
    TS(7);
    grid_barrier();
    TS(8);

    float h00, h01, h10, h11;
    {
        float2 aa = __ldcg(reinterpret_cast<const float2*>(&g_attn_acc[2 * tid]));
        float2 ab = __ldcg(reinterpret_cast<const float2*>(&g_attn_acc[512 + 2 * tid]));
        h00 = bf16r(bf_lo(xv0) + bf16r(aa.x)); h01 = bf16r(bf_hi(xv0) + bf16r(aa.y));
        h10 = bf16r(bf_lo(xv1) + bf16r(ab.x)); h11 = bf16r(bf_hi(xv1) + bf16r(ab.y));
        s_vec[2 * tid] = h00; s_vec[2 * tid + 1] = h01;
        s_vec[512 + 2 * tid] = h10; s_vec[512 + 2 * tid + 1] = h11;
        CTA_SYNC();
        layernorm_2x512(s_vec, s_red, tid);
        if (cta < 112) {
            float f[2][8];
#pragma unroll
            for (int j = 0; j < 8; j++) { f[0][j] = 0.f; f[1][j] = 0.f; }
#pragma unroll
            for (int i = 0; i < 4; i++) {
                int r = (tid >> 1) + 128 * i;
                float n0 = s_vec[r], n1 = s_vec[512 + r];
                uint32_t w[4] = {w1v[i].x, w1v[i].y, w1v[i].z, w1v[i].w};
#pragma unroll
                for (int j = 0; j < 4; j++) {
                    float lo = bf_lo(w[j]), hi = bf_hi(w[j]);
                    f[0][2 * j] += n0 * lo; f[0][2 * j + 1] += n0 * hi;
                    f[1][2 * j] += n1 * lo; f[1][2 * j + 1] += n1 * hi;
                }
            }
#pragma unroll
            for (int o = 2; o < 32; o <<= 1) {
#pragma unroll
                for (int j = 0; j < 8; j++) {
                    f[0][j] += __shfl_xor_sync(0xffffffffu, f[0][j], o);
                    f[1][j] += __shfl_xor_sync(0xffffffffu, f[1][j], o);
                }
            }
            float* s_fp = reinterpret_cast<float*>(ring);
            if (lane < 2) {
#pragma unroll
                for (int j = 0; j < 8; j++) {
                    s_fp[(warp * 2 + 0) * 16 + lane * 8 + j] = f[0][j];
                    s_fp[(warp * 2 + 1) * 16 + lane * 8 + j] = f[1][j];
                }
            }
            CTA_SYNC();
            if (tid < 32) {
                int bb = tid >> 4, c = tid & 15;
                float sacc = 0.f;
#pragma unroll
                for (int w = 0; w < NWARP; w++) sacc += s_fp[(w * 2 + bb) * 16 + c];
                float hh = bf16r(bf16r(sacc) + bias1);
                s_f[tid] = bf16r(gelu_tanh(hh));
            }
            CTA_SYNC();
            float a[2][8];
#pragma unroll
            for (int j = 0; j < 8; j++) { a[0][j] = 0.f; a[1][j] = 0.f; }
#pragma unroll
            for (int i = 0; i < 4; i++) {
                int r = (tid >> 6) + 4 * i;
                float f0 = s_f[r], f1 = s_f[16 + r];
                uint32_t w[4] = {w2v[i].x, w2v[i].y, w2v[i].z, w2v[i].w};
#pragma unroll
                for (int j = 0; j < 4; j++) {
                    float lo = bf_lo(w[j]), hi = bf_hi(w[j]);
                    a[0][2 * j] += f0 * lo; a[0][2 * j + 1] += f0 * hi;
                    a[1][2 * j] += f1 * lo; a[1][2 * j + 1] += f1 * hi;
                }
            }
            float* s_p = reinterpret_cast<float*>(ring) + 1024;
            {
                int g = tid >> 6, c8 = (tid & 63) * 8;
#pragma unroll
                for (int bb = 0; bb < 2; bb++) {
                    float4* dst = reinterpret_cast<float4*>(&s_p[(g * 2 + bb) * 512 + c8]);
                    dst[0] = make_float4(a[bb][0], a[bb][1], a[bb][2], a[bb][3]);
                    dst[1] = make_float4(a[bb][4], a[bb][5], a[bb][6], a[bb][7]);
                }
            }
            CTA_SYNC();
            {
                int bb = tid >> 7, c4 = (tid & 127) * 4;
                float4 acc = make_float4(0.f, 0.f, 0.f, 0.f);
#pragma unroll
                for (int g = 0; g < 4; g++) {
                    float4 v = *reinterpret_cast<float4*>(&s_p[(g * 2 + bb) * 512 + c4]);
                    acc.x += v.x; acc.y += v.y; acc.z += v.z; acc.w += v.w;
                }
                red_v4(&g_out_acc[(cta & 3) * 1024 + bb * 512 + c4], acc.x, acc.y, acc.z, acc.w);
            }
        }
    }
    TS(9);
    __shared__ unsigned s_last;
    CTA_SYNC();
    if (tid == 0) {
        __threadfence();
        unsigned old = atomicAdd(&g_done, 1u);
        s_last = ((old % NCTA) == NCTA - 1) ? 1u : 0u;
        __threadfence();
    }
    CTA_SYNC();
    if (s_last) {
        float2 oa = make_float2(0.f, 0.f), ob = make_float2(0.f, 0.f);
#pragma unroll
        for (int c = 0; c < 4; c++) {
            float2 va = __ldcg(reinterpret_cast<const float2*>(&g_out_acc[c * 1024 + 2 * tid]));
            float2 vb = __ldcg(reinterpret_cast<const float2*>(&g_out_acc[c * 1024 + 512 + 2 * tid]));
            oa.x += va.x; oa.y += va.y; ob.x += vb.x; ob.y += vb.y;
        }
        uint32_t bb = bias2;
        float bl = bf_lo(bb), bhh = bf_hi(bb);
        float r00 = h00 + bf16r(bf16r(oa.x) + bl), r01 = h01 + bf16r(bf16r(oa.y) + bhh);
        float r10 = h10 + bf16r(bf16r(ob.x) + bl), r11 = h11 + bf16r(bf16r(ob.y) + bhh);
        *reinterpret_cast<uint32_t*>(out + 2 * tid) = pack_bf16(r00, r01);
        *reinterpret_cast<uint32_t*>(out + 512 + 2 * tid) = pack_bf16(r10, r11);
        for (int i = tid; i < NB * DM; i += NTHREADS) g_attn_acc[i] = 0.f;
        for (int i = tid; i < 4 * NB * DM; i += NTHREADS) g_out_acc[i] = 0.f;
        if (tid == 0) g_epoch = epoch;
    }
    TS(10);
}

typedef CUresult (*PFN_encodeTiled)(CUtensorMap*, CUtensorMapDataType, cuuint32_t, void*, const cuuint64_t*,
                                    const cuuint64_t*, const cuuint32_t*, const cuuint32_t*, CUtensorMapInterleave,
                                    CUtensorMapSwizzle, CUtensorMapL2promotion, CUtensorMapFloatOOBfill);

}

extern "C" void kernel_launch(void* const* d_in, const int* in_sizes, int n_in, void* d_out, int out_size) {
    static PFN_encodeTiled enc = nullptr;
    if (!enc) {
        void* fn = nullptr;
        cudaDriverEntryPointQueryResult qres;
        cudaGetDriverEntryPoint("cuTensorMapEncodeTiled", &fn, cudaEnableDefault, &qres);
        enc = (PFN_encodeTiled)fn;
        cudaFuncSetAttribute(fused_kernel, cudaFuncAttributeMaxDynamicSharedMemorySize, SMEM_BYTES);
    }
    CUtensorMap mapK, mapV;
    cuuint64_t gdim[2] = {(cuuint64_t)DH, (cuuint64_t)NB * HKV * SK};
    cuuint64_t gstr[1] = {(cuuint64_t)DH * 2};
    cuuint32_t box[2] = {64, 16};
    cuuint32_t estr[2] = {1, 1};
    enc(&mapK, CU_TENSOR_MAP_DATA_TYPE_BFLOAT16, 2, d_in[1], gdim, gstr, box, estr, CU_TENSOR_MAP_INTERLEAVE_NONE,
        CU_TENSOR_MAP_SWIZZLE_128B, CU_TENSOR_MAP_L2_PROMOTION_L2_128B, CU_TENSOR_MAP_FLOAT_OOB_FILL_NONE);
    enc(&mapV, CU_TENSOR_MAP_DATA_TYPE_BFLOAT16, 2, d_in[2], gdim, gstr, box, estr, CU_TENSOR_MAP_INTERLEAVE_NONE,
        CU_TENSOR_MAP_SWIZZLE_128B, CU_TENSOR_MAP_L2_PROMOTION_L2_128B, CU_TENSOR_MAP_FLOAT_OOB_FILL_NONE);
    fused_kernel<<<NCTA, NTHREADS, SMEM_BYTES>>>(
        mapK, mapV, (const __nv_bfloat16*)d_in[0], (const __nv_bfloat16*)d_in[3], (const __nv_bfloat16*)d_in[4],
        (const __nv_bfloat16*)d_in[6], (const __nv_bfloat16*)d_in[7], (const __nv_bfloat16*)d_in[8],
        (const __nv_bfloat16*)d_in[9], (__nv_bfloat16*)d_out);
}
```

```cpp
#include <cuda_runtime.h>
#include <cuda_bf16.h>
#include <cuda.h>
#include <stdint.h>

namespace {

constexpr int NB = 2, DM = 512, HQ = 32, HKV = 8, SK = 8192, DH = 128, FF = 1792;
constexpr int NCTA = 128, NSPLIT = 8, KEYS_PER_CTA = SK / NSPLIT;
constexpr int NWARP = 8, NTHREADS = NWARP * 32;
constexpr int NSTAGE = 3;
#define QTRIES (1 << 20)
#define QSLEEP 400
#define PRE_STAGES 0
constexpr int STAGE_BYTES = 8192;
constexpr int NBLK = KEYS_PER_CTA / (16 * NWARP);
constexpr int RING_BYTES = NWARP * NSTAGE * STAGE_BYTES;
constexpr int SMEM_BYTES = RING_BYTES + 4096 + 2048 + 1024;

__device__ unsigned long long g_q64[NB * HQ * DH / 2];
__device__ unsigned g_epoch;
__device__ unsigned long long g_pm[16 * NSPLIT * 4];
__device__ unsigned long long g_pl[16 * NSPLIT * 4];
__device__ unsigned long long g_po[16 * NSPLIT * 4 * DH];
__device__ float g_attn_acc[NB * DM];
__device__ float g_out_acc[4 * NB * DM];
__device__ unsigned g_bar;
__device__ unsigned g_done;

#define TS(i)
#define CTA_SYNC() asm volatile("bar.sync 1, 256;" ::: "memory")
__device__ __forceinline__ uint32_t smem_u32(const void* p) {
    return (uint32_t)__cvta_generic_to_shared(p);
}
__device__ __forceinline__ float bf16r(float x) {
    return __bfloat162float(__float2bfloat16_rn(x));
}
__device__ __forceinline__ uint32_t pack_bf16(float lo, float hi) {
    __nv_bfloat162 v = __floats2bfloat162_rn(lo, hi);
    return *reinterpret_cast<uint32_t*>(&v);
}
__device__ __forceinline__ float bf_lo(uint32_t v) { return __uint_as_float(v << 16); }
__device__ __forceinline__ float bf_hi(uint32_t v) { return __uint_as_float(v & 0xffff0000u); }

__device__ __forceinline__ void mbar_init(uint32_t bar, uint32_t cnt) {
    asm volatile("mbarrier.init.shared::cta.b64 [%0], %1;" ::"r"(bar), "r"(cnt) : "memory");
}
__device__ __forceinline__ void mbar_expect_tx(uint32_t bar, uint32_t bytes) {
    asm volatile("mbarrier.arrive.expect_tx.shared::cta.b64 _, [%0], %1;" ::"r"(bar), "r"(bytes) : "memory");
}
__device__ __forceinline__ void mbar_wait(uint32_t bar, uint32_t parity) {
    for (int i = 0; i < (1 << 22); i++) {
        uint32_t ok;
        asm volatile(
            "{\n"
            ".reg .pred p;\n"
            "mbarrier.try_wait.parity.shared::cta.b64 p, [%1], %2;\n"
            "selp.u32 %0, 1, 0, p;\n"
            "}\n" : "=r"(ok) : "r"(bar), "r"(parity) : "memory");
        if (ok) break;
    }
}
__device__ __forceinline__ void tma_2d(uint32_t dst, const CUtensorMap* map, uint32_t bar, int c0, int c1) {
    asm volatile(
        "cp.async.bulk.tensor.2d.shared::cluster.global.mbarrier::complete_tx::bytes [%0], [%1, {%3, %4}], [%2];"
        ::"r"(dst), "l"(map), "r"(bar), "r"(c0), "r"(c1) : "memory");
}
__device__ __forceinline__ void ldsm_x4(uint32_t addr, uint32_t& r0, uint32_t& r1, uint32_t& r2, uint32_t& r3) {
    asm volatile("ldmatrix.sync.aligned.m8n8.x4.shared.b16 {%0,%1,%2,%3}, [%4];"
                 : "=r"(r0), "=r"(r1), "=r"(r2), "=r"(r3) : "r"(addr) : "memory");
}
__device__ __forceinline__ void ldsm_x4_t(uint32_t addr, uint32_t& r0, uint32_t& r1, uint32_t& r2, uint32_t& r3) {
    asm volatile("ldmatrix.sync.aligned.m8n8.x4.trans.shared.b16 {%0,%1,%2,%3}, [%4];"
                 : "=r"(r0), "=r"(r1), "=r"(r2), "=r"(r3) : "r"(addr) : "memory");
}
__device__ __forceinline__ void mma16816(float* c, uint32_t a0, uint32_t a1, uint32_t a2, uint32_t a3,
                                         uint32_t b0, uint32_t b1) {
    asm volatile(
        "mma.sync.aligned.m16n8k16.row.col.f32.bf16.bf16.f32 {%0,%1,%2,%3}, {%4,%5,%6,%7}, {%8,%9}, {%0,%1,%2,%3};"
        : "+f"(c[0]), "+f"(c[1]), "+f"(c[2]), "+f"(c[3])
        : "r"(a0), "r"(a1), "r"(a2), "r"(a3), "r"(b0), "r"(b1));
}
__device__ __forceinline__ unsigned ld_acquire(const unsigned* p) {
    unsigned v;
    asm volatile("ld.acquire.gpu.global.u32 %0, [%1];" : "=r"(v) : "l"(p) : "memory");
    return v;
}
__device__ __forceinline__ uint4 ldg_nc_v4(const void* p) {
    uint4 v;
    asm volatile("ld.global.nc.L1::no_allocate.v4.u32 {%0,%1,%2,%3}, [%4];"
                 : "=r"(v.x), "=r"(v.y), "=r"(v.z), "=r"(v.w) : "l"(p));
    return v;
}
__device__ __forceinline__ uint32_t ldg_nc_u32(const void* p) {
    uint32_t v;
    asm volatile("ld.global.nc.L1::no_allocate.u32 %0, [%1];" : "=r"(v) : "l"(p));
    return v;
}

__device__ __forceinline__ void red_v4(float* p, float a, float b, float c, float d) {
    asm volatile("red.global.add.v4.f32 [%0], {%1,%2,%3,%4};" ::"l"(p), "f"(a), "f"(b), "f"(c), "f"(d) : "memory");
}

__device__ __forceinline__ void st_tag(unsigned long long* p, float v, unsigned tag) {
    unsigned long long w = ((unsigned long long)tag << 32) | __float_as_uint(v);
    asm volatile("st.relaxed.gpu.global.u64 [%0], %1;" ::"l"(p), "l"(w) : "memory");
}
__device__ __forceinline__ unsigned long long ld_tag(const unsigned long long* p) {
    unsigned long long w;
    asm volatile("ld.relaxed.gpu.global.u64 %0, [%1];" : "=l"(w) : "l"(p) : "memory");
    return w;
}

__device__ __forceinline__ void grid_barrier() {
    CTA_SYNC();
    if (threadIdx.x == 0) {
        __threadfence();
        unsigned old = atomicAdd(&g_bar, 1u);
        unsigned target = (old / NCTA + 1u) * NCTA;
        unsigned iters = 0;
        while ((int)(ld_acquire(&g_bar) - target) < 0) {
            if (++iters > 2000000u) break;
        }
        __threadfence();
    }
    CTA_SYNC();
}

__device__ __forceinline__ void layernorm_2x512(float* v, float* red, int tid) {
    int warp = tid >> 5, lane = tid & 31;
    float a0 = v[2 * tid], a1 = v[2 * tid + 1], b0 = v[512 + 2 * tid], b1 = v[512 + 2 * tid + 1];
    float sa = a0 + a1, sb = b0 + b1;
#pragma unroll
    for (int o = 16; o > 0; o >>= 1) {
        sa += __shfl_xor_sync(0xffffffffu, sa, o);
        sb += __shfl_xor_sync(0xffffffffu, sb, o);
    }
    if (lane == 0) { red[warp] = sa; red[8 + warp] = sb; }
    CTA_SYNC();
    float ma = 0.f, mb = 0.f;
#pragma unroll
    for (int w = 0; w < 8; w++) { ma += red[w]; mb += red[8 + w]; }
    ma *= (1.f / 512.f); mb *= (1.f / 512.f);
    float da0 = a0 - ma, da1 = a1 - ma, db0 = b0 - mb, db1 = b1 - mb;
    float va = da0 * da0 + da1 * da1, vb = db0 * db0 + db1 * db1;
#pragma unroll
    for (int o = 16; o > 0; o >>= 1) {
        va += __shfl_xor_sync(0xffffffffu, va, o);
        vb += __shfl_xor_sync(0xffffffffu, vb, o);
    }
    CTA_SYNC();
    if (lane == 0) { red[16 + warp] = va; red[24 + warp] = vb; }
    CTA_SYNC();
    va = 0.f; vb = 0.f;
#pragma unroll
    for (int w = 0; w < 8; w++) { va += red[16 + w]; vb += red[24 + w]; }
    va = bf16r(va * (1.f / 512.f)); vb = bf16r(vb * (1.f / 512.f));
    float mra = bf16r(ma), mrb = bf16r(mb);
    float sda = bf16r(sqrtf(bf16r(va + 1e-5f))), sdb = bf16r(sqrtf(bf16r(vb + 1e-5f)));
    v[2 * tid] = bf16r(bf16r(a0 - mra) / sda);
    v[2 * tid + 1] = bf16r(bf16r(a1 - mra) / sda);
    v[512 + 2 * tid] = bf16r(bf16r(b0 - mrb) / sdb);
    v[512 + 2 * tid + 1] = bf16r(bf16r(b1 - mrb) / sdb);
    CTA_SYNC();
}

__device__ __forceinline__ float gelu_tanh(float x) {
    const float k0 = 0.7978845608028654f, k1 = 0.044715f;
    float inner = k0 * (x + k1 * x * x * x);
    return 0.5f * x * (1.f + tanhf(inner));
}

__global__ void __launch_bounds__(NTHREADS, 1)
fused_kernel(const __grid_constant__ CUtensorMap mapK, const __grid_constant__ CUtensorMap mapV,
             const __nv_bfloat16* __restrict__ x, const __nv_bfloat16* __restrict__ wq,
             const __nv_bfloat16* __restrict__ wo, const __nv_bfloat16* __restrict__ w1,
             const __nv_bfloat16* __restrict__ b1, const __nv_bfloat16* __restrict__ w2,
             const __nv_bfloat16* __restrict__ b2, __nv_bfloat16* __restrict__ out) {
    extern __shared__ __align__(1024) uint8_t smem_raw[];
    uint8_t* smem = smem_raw + ((1024u - (smem_u32(smem_raw) & 1023u)) & 1023u);
    uint8_t* ring = smem;
    uint64_t* bars = reinterpret_cast<uint64_t*>(smem + RING_BYTES);
    float* s_vec = reinterpret_cast<float*>(smem + RING_BYTES + 256);
    float* s_red = reinterpret_cast<float*>(smem + RING_BYTES + 256 + 4096);
    float* s_o = s_red + 64;
    float* s_f = s_o + 64;

    const int tid = threadIdx.x, warp = tid >> 5, lane = tid & 31;
    const int cta = blockIdx.x;
    const int bh = cta >> 3, split = cta & 7;
    const int b = bh >> 3, kvh = bh & 7;

    TS(0);
    const uint32_t ring_w = smem_u32(ring) + warp * (NSTAGE * STAGE_BYTES);
    const uint32_t bar_w = smem_u32(bars) + warp * (NSTAGE * 8);
    if (lane == 0) {
#pragma unroll
        for (int s = 0; s < NSTAGE; s++) mbar_init(bar_w + s * 8, 1);
        asm volatile("fence.mbarrier_init.release.cluster;" ::: "memory");
    }
    __syncwarp();
    const unsigned epoch = __ldcg(&g_epoch) + 1u;
    uint32_t xv0 = ldg_nc_u32(x + 2 * tid);
    uint32_t xv1 = ldg_nc_u32(x + 512 + 2 * tid);
    uint4 wqv[8];
    {
        const __nv_bfloat16* p = wq + (size_t)(tid >> 2) * (HQ * DH) + cta * 32 + (tid & 3) * 8;
#pragma unroll
        for (int i = 0; i < 8; i++) wqv[i] = ldg_nc_v4(p + (size_t)i * 64 * (HQ * DH));
    }
    const int row0 = bh * SK + split * KEYS_PER_CTA + warp * 16;
    auto issue_stage = [&](int blk) {
        const int s = blk % NSTAGE;
        uint32_t dst = ring_w + s * STAGE_BYTES;
        uint32_t bar = bar_w + s * 8;
        int r = row0 + blk * 128;
        mbar_expect_tx(bar, STAGE_BYTES);
        tma_2d(dst, &mapK, bar, 0, r);
        tma_2d(dst + 2048, &mapK, bar, 64, r);
        tma_2d(dst + 4096, &mapV, bar, 0, r);
        tma_2d(dst + 6144, &mapV, bar, 64, r);
    };
    if (lane == 0) {
#pragma unroll
        for (int s = 0; s < PRE_STAGES; s++) issue_stage(s);
    }
    uint4 wov[8];
    uint4 w1v[4];
    uint4 w2v[4];
    const __nv_bfloat16* wo_p = wo + (size_t)((cta >> 2) * 128 + (tid >> 4)) * DM + (cta & 3) * 128 + (tid & 15) * 8;
    const int fcta = cta < 112 ? cta : 0;
    const __nv_bfloat16* w1_p = w1 + (size_t)(tid >> 1) * FF + fcta * 16 + (tid & 1) * 8;
    const float bias1 = __bfloat162float(b1[fcta * 16 + (tid & 15)]);
    const uint32_t bias2 = *reinterpret_cast<const uint32_t*>(b2 + 2 * tid);
    const __nv_bfloat16* w2_p = w2 + (size_t)(fcta * 16 + (tid >> 6)) * DM + (tid & 63) * 8;

    TS(1);
    s_vec[2 * tid] = bf_lo(xv0); s_vec[2 * tid + 1] = bf_hi(xv0);
    s_vec[512 + 2 * tid] = bf_lo(xv1); s_vec[512 + 2 * tid + 1] = bf_hi(xv1);
    CTA_SYNC();
    layernorm_2x512(s_vec, s_red, tid);

    {
        float acc[2][8];
#pragma unroll
        for (int i = 0; i < 8; i++) { acc[0][i] = 0.f; acc[1][i] = 0.f; }
#pragma unroll
        for (int i = 0; i < 8; i++) {
            int r = (tid >> 2) + i * 64;
            float x0 = s_vec[r], x1 = s_vec[512 + r];
            uint32_t w[4] = {wqv[i].x, wqv[i].y, wqv[i].z, wqv[i].w};
#pragma unroll
            for (int j = 0; j < 4; j++) {
                float lo = bf_lo(w[j]), hi = bf_hi(w[j]);
                acc[0][2 * j] += x0 * lo; acc[0][2 * j + 1] += x0 * hi;
                acc[1][2 * j] += x1 * lo; acc[1][2 * j + 1] += x1 * hi;
            }
        }
        if (lane == 0) {
#pragma unroll
            for (int s = PRE_STAGES; s < NSTAGE; s++) issue_stage(s);
        }
#pragma unroll
        for (int o = 4; o < 32; o <<= 1) {
#pragma unroll
            for (int i = 0; i < 8; i++) {
                acc[0][i] += __shfl_xor_sync(0xffffffffu, acc[0][i], o);
                acc[1][i] += __shfl_xor_sync(0xffffffffu, acc[1][i], o);
            }
        }
        __shared__ float s_qpart[NWARP][2][32];
        if (lane < 4) {
#pragma unroll
            for (int i = 0; i < 8; i++) {
                s_qpart[warp][0][lane * 8 + i] = acc[0][i];
                s_qpart[warp][1][lane * 8 + i] = acc[1][i];
            }
        }
        CTA_SYNC();
        if (tid < 32) {
            int bb = tid >> 4, c = (tid & 15) * 2;
            float s0 = 0.f, s1 = 0.f;
#pragma unroll
            for (int w = 0; w < NWARP; w++) { s0 += s_qpart[w][bb][c]; s1 += s_qpart[w][bb][c + 1]; }
            unsigned long long v = ((unsigned long long)epoch << 32) | pack_bf16(s0, s1);
            asm volatile("st.relaxed.gpu.global.u64 [%0], %1;" ::"l"(&g_q64[(bb * (HQ * DH) + cta * 32 + c) >> 1]), "l"(v) : "memory");
        }
    }
    TS(2);

    uint32_t qa[8][2];
    {
        int hl = lane >> 2;
        const unsigned long long* qp = g_q64 + ((b * (HQ * DH) + (kvh * 4 + (hl & 3)) * DH + (lane & 3) * 2) >> 1);
        for (int tries = 0; tries < (1 << 20); tries++) {
            bool ok = true;
#pragma unroll
            for (int ks = 0; ks < 8; ks++) {
                unsigned long long v0, v1;
                asm volatile("ld.relaxed.gpu.global.u64 %0, [%1];" : "=l"(v0) : "l"(qp + ks * 8) : "memory");
                asm volatile("ld.relaxed.gpu.global.u64 %0, [%1];" : "=l"(v1) : "l"(qp + ks * 8 + 4) : "memory");
                ok = ok && ((unsigned)(v0 >> 32) == epoch) && ((unsigned)(v1 >> 32) == epoch);
                qa[ks][0] = hl < 4 ? (uint32_t)v0 : 0u;
                qa[ks][1] = hl < 4 ? (uint32_t)v1 : 0u;
            }
            if (__all_sync(0xffffffffu, ok)) break;
            __nanosleep(QSLEEP);
        }
    }
    TS(3);
    float oacc[16][4];
#pragma unroll
    for (int j = 0; j < 16; j++) { oacc[j][0] = 0.f; oacc[j][1] = 0.f; oacc[j][2] = 0.f; oacc[j][3] = 0.f; }
    float m_run = -INFINITY, l_run = 0.f;
    const float scale = 0.08838834764831845f;
    const float LOG2E = 1.4426950408889634f;

    const int lrow = lane & 7, lmat = lane >> 3;
    const int k_row = (lmat >> 1) * 8 + lrow;
    const int k_cofs = lmat & 1;
    const int v_row = (lmat & 1) * 8 + lrow;
    const int v_cofs = lmat >> 1;

#pragma unroll
    for (int it = 0; it < NBLK; it++) {
        wov[it] = ldg_nc_v4(wo_p + (size_t)it * 16 * DM);
        if (it < 4) w1v[it] = ldg_nc_v4(w1_p + (size_t)it * 128 * FF);
        else w2v[it - 4] = ldg_nc_v4(w2_p + (size_t)(it - 4) * 4 * DM);
        const int s = it % NSTAGE;
        const uint32_t parity = (it / NSTAGE) & 1;
        const uint32_t st = ring_w + s * STAGE_BYTES;
        mbar_wait(bar_w + s * 8, parity);

        float sc[2][4];
#pragma unroll
        for (int j = 0; j < 2; j++) { sc[j][0] = 0.f; sc[j][1] = 0.f; sc[j][2] = 0.f; sc[j][3] = 0.f; }
#pragma unroll
        for (int ks = 0; ks < 8; ks++) {
            int chunk = (ks & 3) * 2 + k_cofs;
            uint32_t addr = st + (ks >> 2) * 2048 + k_row * 128 + ((chunk ^ (k_row & 7)) << 4);
            uint32_t r0, r1, r2, r3;
            ldsm_x4(addr, r0, r1, r2, r3);
            mma16816(sc[0], qa[ks][0], 0u, qa[ks][1], 0u, r0, r1);
            mma16816(sc[1], qa[ks][0], 0u, qa[ks][1], 0u, r2, r3);
        }
        float v00 = bf16r(bf16r(sc[0][0]) * scale), v01 = bf16r(bf16r(sc[0][1]) * scale);
        float v10 = bf16r(bf16r(sc[1][0]) * scale), v11 = bf16r(bf16r(sc[1][1]) * scale);
        float mx = fmaxf(fmaxf(v00, v01), fmaxf(v10, v11));
        mx = fmaxf(mx, __shfl_xor_sync(0xffffffffu, mx, 1));
        mx = fmaxf(mx, __shfl_xor_sync(0xffffffffu, mx, 2));
        float m_new = fmaxf(m_run, mx);
        float corr = exp2f((m_run - m_new) * LOG2E);
        float p00 = exp2f((v00 - m_new) * LOG2E), p01 = exp2f((v01 - m_new) * LOG2E);
        float p10 = exp2f((v10 - m_new) * LOG2E), p11 = exp2f((v11 - m_new) * LOG2E);
        l_run = l_run * corr + (p00 + p01 + p10 + p11);
        m_run = m_new;
        uint32_t pa0 = pack_bf16(p00, p01), pa2 = pack_bf16(p10, p11);
#pragma unroll
        for (int j = 0; j < 16; j++) { oacc[j][0] *= corr; oacc[j][1] *= corr; }
#pragma unroll
        for (int jj = 0; jj < 8; jj++) {
            int chunk = (jj & 3) * 2 + v_cofs;
            uint32_t addr = st + 4096 + (jj >> 2) * 2048 + v_row * 128 + ((chunk ^ (v_row & 7)) << 4);
            uint32_t r0, r1, r2, r3;
            ldsm_x4_t(addr, r0, r1, r2, r3);
            mma16816(oacc[2 * jj], pa0, 0u, pa2, 0u, r0, r1);
            mma16816(oacc[2 * jj + 1], pa0, 0u, pa2, 0u, r2, r3);
        }
        __syncwarp();
        if (lane == 0 && it + NSTAGE < NBLK) issue_stage(it + NSTAGE);
    }
    TS(4);
    l_run += __shfl_xor_sync(0xffffffffu, l_run, 1);
    l_run += __shfl_xor_sync(0xffffffffu, l_run, 2);

    CTA_SYNC();
    float* r_o = reinterpret_cast<float*>(ring);
    float* r_m = reinterpret_cast<float*>(ring + 16384);
    float* r_l = r_m + 32;
    if (lane < 16) {
        int hl = lane >> 2;
#pragma unroll
        for (int j = 0; j < 16; j++) {
            float2 v = make_float2(oacc[j][0], oacc[j][1]);
            *reinterpret_cast<float2*>(&r_o[(warp * 4 + hl) * DH + j * 8 + (lane & 3) * 2]) = v;
        }
        if ((lane & 3) == 0) { r_m[warp * 4 + hl] = m_run; r_l[warp * 4 + hl] = l_run; }
    }
    CTA_SYNC();
    {
        int hl = tid >> 6, d = (tid & 63) * 2;
        float mm = -INFINITY;
#pragma unroll
        for (int w = 0; w < NWARP; w++) mm = fmaxf(mm, r_m[w * 4 + hl]);
        float o0 = 0.f, o1 = 0.f, ll = 0.f;
#pragma unroll
        for (int w = 0; w < NWARP; w++) {
            float c = exp2f((r_m[w * 4 + hl] - mm) * LOG2E);
            float2 v = *reinterpret_cast<float2*>(&r_o[(w * 4 + hl) * DH + d]);
            o0 += c * v.x; o1 += c * v.y; ll += c * r_l[w * 4 + hl];
        }
        int pidx = (cta * 4 + hl);
        st_tag(&g_po[(size_t)pidx * DH + d], o0, epoch);
        st_tag(&g_po[(size_t)pidx * DH + d + 1], o1, epoch);
        if ((tid & 63) == 0) { st_tag(&g_pm[pidx], mm, epoch); st_tag(&g_pl[pidx], ll, epoch); }
    }
    TS(5);

    {
        int head = cta >> 2;
        int kv = head >> 2, hl = head & 3;
        {
            int bb = tid >> 7, d = tid & 127;
            int base = ((bb * 8 + kv) * NSPLIT) * 4 + hl;
            float pm[NSPLIT], pl[NSPLIT], po[NSPLIT];
            for (int tries = 0; tries < (1 << 20); tries++) {
                bool ok = true;
#pragma unroll
                for (int s = 0; s < NSPLIT; s++) {
                    unsigned long long a0 = ld_tag(&g_pm[base + s * 4]);
                    unsigned long long a1 = ld_tag(&g_pl[base + s * 4]);
                    unsigned long long a2 = ld_tag(&g_po[(size_t)(base + s * 4) * DH + d]);
                    ok = ok && ((unsigned)(a0 >> 32) == epoch) && ((unsigned)(a1 >> 32) == epoch) && ((unsigned)(a2 >> 32) == epoch);
                    pm[s] = __uint_as_float((unsigned)a0); pl[s] = __uint_as_float((unsigned)a1); po[s] = __uint_as_float((unsigned)a2);
                }
                if (ok) break;
                __nanosleep(64);
            }
            TS(6);
            float mm = -INFINITY;
#pragma unroll
            for (int s = 0; s < NSPLIT; s++) mm = fmaxf(mm, pm[s]);
            float oo = 0.f, ll = 0.f;
#pragma unroll
            for (int s = 0; s < NSPLIT; s++) {
                float c = exp2f((pm[s] - mm) * LOG2E);
                oo += c * po[s]; ll += c * pl[s];
            }
            s_vec[tid] = bf16r(oo / ll);
        }
        CTA_SYNC();
        float a[2][8];
#pragma unroll
        for (int j = 0; j < 8; j++) { a[0][j] = 0.f; a[1][j] = 0.f; }
#pragma unroll
        for (int i = 0; i < 8; i++) {
            int r = (tid >> 4) + 16 * i;
            float o0 = s_vec[r], o1 = s_vec[128 + r];
            uint32_t w[4] = {wov[i].x, wov[i].y, wov[i].z, wov[i].w};
#pragma unroll
            for (int j = 0; j < 4; j++) {
                float lo = bf_lo(w[j]), hi = bf_hi(w[j]);
                a[0][2 * j] += o0 * lo; a[0][2 * j + 1] += o0 * hi;
                a[1][2 * j] += o1 * lo; a[1][2 * j + 1] += o1 * hi;
            }
        }
#pragma unroll
        for (int j = 0; j < 8; j++) {
            a[0][j] += __shfl_xor_sync(0xffffffffu, a[0][j], 16);
            a[1][j] += __shfl_xor_sync(0xffffffffu, a[1][j], 16);
        }
        float* s_p = reinterpret_cast<float*>(ring);
        if (lane < 16) {
#pragma unroll
            for (int bb = 0; bb < 2; bb++) {
                float4* dst = reinterpret_cast<float4*>(&s_p[(warp * 2 + bb) * 128 + lane * 8]);
                dst[0] = make_float4(a[bb][0], a[bb][1], a[bb][2], a[bb][3]);
                dst[1] = make_float4(a[bb][4], a[bb][5], a[bb][6], a[bb][7]);
            }
        }
        CTA_SYNC();
        if (tid < 64) {
            int bb = tid >> 5, c4 = (tid & 31) * 4;
            float4 acc = make_float4(0.f, 0.f, 0.f, 0.f);
#pragma unroll
            for (int w = 0; w < NWARP; w++) {
                float4 v = *reinterpret_cast<float4*>(&s_p[(w * 2 + bb) * 128 + c4]);
                acc.x += v.x; acc.y += v.y; acc.z += v.z; acc.w += v.w;
            }
            red_v4(&g_attn_acc[bb * 512 + (cta & 3) * 128 + c4], acc.x, acc.y, acc.z, acc.w);
        }
    }
    TS(7);
    grid_barrier();
    TS(8);

    float h00, h01, h10, h11;
    {
        float2 aa = __ldcg(reinterpret_cast<const float2*>(&g_attn_acc[2 * tid]));
        float2 ab = __ldcg(reinterpret_cast<const float2*>(&g_attn_acc[512 + 2 * tid]));
        h00 = bf16r(bf_lo(xv0) + bf16r(aa.x)); h01 = bf16r(bf_hi(xv0) + bf16r(aa.y));
        h10 = bf16r(bf_lo(xv1) + bf16r(ab.x)); h11 = bf16r(bf_hi(xv1) + bf16r(ab.y));
        s_vec[2 * tid] = h00; s_vec[2 * tid + 1] = h01;
        s_vec[512 + 2 * tid] = h10; s_vec[512 + 2 * tid + 1] = h11;
        CTA_SYNC();
        layernorm_2x512(s_vec, s_red, tid);
        if (cta < 112) {
            float f[2][8];
#pragma unroll
            for (int j = 0; j < 8; j++) { f[0][j] = 0.f; f[1][j] = 0.f; }
#pragma unroll
            for (int i = 0; i < 4; i++) {
                int r = (tid >> 1) + 128 * i;
                float n0 = s_vec[r], n1 = s_vec[512 + r];
                uint32_t w[4] = {w1v[i].x, w1v[i].y, w1v[i].z, w1v[i].w};
#pragma unroll
                for (int j = 0; j < 4; j++) {
                    float lo = bf_lo(w[j]), hi = bf_hi(w[j]);
                    f[0][2 * j] += n0 * lo; f[0][2 * j + 1] += n0 * hi;
                    f[1][2 * j] += n1 * lo; f[1][2 * j + 1] += n1 * hi;
                }
            }
#pragma unroll
            for (int o = 2; o < 32; o <<= 1) {
#pragma unroll
                for (int j = 0; j < 8; j++) {
                    f[0][j] += __shfl_xor_sync(0xffffffffu, f[0][j], o);
                    f[1][j] += __shfl_xor_sync(0xffffffffu, f[1][j], o);
                }
            }
            float* s_fp = reinterpret_cast<float*>(ring);
            if (lane < 2) {
#pragma unroll
                for (int j = 0; j < 8; j++) {
                    s_fp[(warp * 2 + 0) * 16 + lane * 8 + j] = f[0][j];
                    s_fp[(warp * 2 + 1) * 16 + lane * 8 + j] = f[1][j];
                }
            }
            CTA_SYNC();
            if (tid < 32) {
                int bb = tid >> 4, c = tid & 15;
                float sacc = 0.f;
#pragma unroll
                for (int w = 0; w < NWARP; w++) sacc += s_fp[(w * 2 + bb) * 16 + c];
                float hh = bf16r(bf16r(sacc) + bias1);
                s_f[tid] = bf16r(gelu_tanh(hh));
            }
            CTA_SYNC();
            float a[2][8];
#pragma unroll
            for (int j = 0; j < 8; j++) { a[0][j] = 0.f; a[1][j] = 0.f; }
#pragma unroll
            for (int i = 0; i < 4; i++) {
                int r = (tid >> 6) + 4 * i;
                float f0 = s_f[r], f1 = s_f[16 + r];
                uint32_t w[4] = {w2v[i].x, w2v[i].y, w2v[i].z, w2v[i].w};
#pragma unroll
                for (int j = 0; j < 4; j++) {
                    float lo = bf_lo(w[j]), hi = bf_hi(w[j]);
                    a[0][2 * j] += f0 * lo; a[0][2 * j + 1] += f0 * hi;
                    a[1][2 * j] += f1 * lo; a[1][2 * j + 1] += f1 * hi;
                }
            }
            float* s_p = reinterpret_cast<float*>(ring) + 1024;
            {
                int g = tid >> 6, c8 = (tid & 63) * 8;
#pragma unroll
                for (int bb = 0; bb < 2; bb++) {
                    float4* dst = reinterpret_cast<float4*>(&s_p[(g * 2 + bb) * 512 + c8]);
                    dst[0] = make_float4(a[bb][0], a[bb][1], a[bb][2], a[bb][3]);
                    dst[1] = make_float4(a[bb][4], a[bb][5], a[bb][6], a[bb][7]);
                }
            }
            CTA_SYNC();
            {
                int bb = tid >> 7, c4 = (tid & 127) * 4;
                float4 acc = make_float4(0.f, 0.f, 0.f, 0.f);
#pragma unroll
                for (int g = 0; g < 4; g++) {
                    float4 v = *reinterpret_cast<float4*>(&s_p[(g * 2 + bb) * 512 + c4]);
                    acc.x += v.x; acc.y += v.y; acc.z += v.z; acc.w += v.w;
                }
                red_v4(&g_out_acc[(cta & 3) * 1024 + bb * 512 + c4], acc.x, acc.y, acc.z, acc.w);
            }
        }
    }
    TS(9);
    __shared__ unsigned s_last;
    CTA_SYNC();
    if (tid == 0) {
        __threadfence();
        unsigned old = atomicAdd(&g_done, 1u);
        s_last = ((old % NCTA) == NCTA - 1) ? 1u : 0u;
        __threadfence();
    }
    CTA_SYNC();
    if (s_last) {
        float2 oa = make_float2(0.f, 0.f), ob = make_float2(0.f, 0.f);
#pragma unroll
        for (int c = 0; c < 4; c++) {
            float2 va = __ldcg(reinterpret_cast<const float2*>(&g_out_acc[c * 1024 + 2 * tid]));
            float2 vb = __ldcg(reinterpret_cast<const float2*>(&g_out_acc[c * 1024 + 512 + 2 * tid]));
            oa.x += va.x; oa.y += va.y; ob.x += vb.x; ob.y += vb.y;
        }
        uint32_t bb = bias2;
        float bl = bf_lo(bb), bhh = bf_hi(bb);
        float r00 = h00 + bf16r(bf16r(oa.x) + bl), r01 = h01 + bf16r(bf16r(oa.y) + bhh);
        float r10 = h10 + bf16r(bf16r(ob.x) + bl), r11 = h11 + bf16r(bf16r(ob.y) + bhh);
        *reinterpret_cast<uint32_t*>(out + 2 * tid) = pack_bf16(r00, r01);
        *reinterpret_cast<uint32_t*>(out + 512 + 2 * tid) = pack_bf16(r10, r11);
        for (int i = tid; i < NB * DM; i += NTHREADS) g_attn_acc[i] = 0.f;
        for (int i = tid; i < 4 * NB * DM; i += NTHREADS) g_out_acc[i] = 0.f;
        if (tid == 0) g_epoch = epoch;
    }
    TS(10);
}

typedef CUresult (*PFN_encodeTiled)(CUtensorMap*, CUtensorMapDataType, cuuint32_t, void*, const cuuint64_t*,
                                    const cuuint64_t*, const cuuint32_t*, const cuuint32_t*, CUtensorMapInterleave,
                                    CUtensorMapSwizzle, CUtensorMapL2promotion, CUtensorMapFloatOOBfill);

}

extern "C" void kernel_launch(void* const* d_in, const int* in_sizes, int n_in, void* d_out, int out_size) {
    static PFN_encodeTiled enc = nullptr;
    if (!enc) {
        void* fn = nullptr;
        cudaDriverEntryPointQueryResult qres;
        cudaGetDriverEntryPoint("cuTensorMapEncodeTiled", &fn, cudaEnableDefault, &qres);
        enc = (PFN_encodeTiled)fn;
        cudaFuncSetAttribute(fused_kernel, cudaFuncAttributeMaxDynamicSharedMemorySize, SMEM_BYTES);
    }
    CUtensorMap mapK, mapV;
    cuuint64_t gdim[2] = {(cuuint64_t)DH, (cuuint64_t)NB * HKV * SK};
    cuuint64_t gstr[1] = {(cuuint64_t)DH * 2};
    cuuint32_t box[2] = {64, 16};
    cuuint32_t estr[2] = {1, 1};
    enc(&mapK, CU_TENSOR_MAP_DATA_TYPE_BFLOAT16, 2, d_in[1], gdim, gstr, box, estr, CU_TENSOR_MAP_INTERLEAVE_NONE,
        CU_TENSOR_MAP_SWIZZLE_128B, CU_TENSOR_MAP_L2_PROMOTION_L2_128B, CU_TENSOR_MAP_FLOAT_OOB_FILL_NONE);
    enc(&mapV, CU_TENSOR_MAP_DATA_TYPE_BFLOAT16, 2, d_in[2], gdim, gstr, box, estr, CU_TENSOR_MAP_INTERLEAVE_NONE,
        CU_TENSOR_MAP_SWIZZLE_128B, CU_TENSOR_MAP_L2_PROMOTION_L2_128B, CU_TENSOR_MAP_FLOAT_OOB_FILL_NONE);
    fused_kernel<<<NCTA, NTHREADS, SMEM_BYTES>>>(
        mapK, mapV, (const __nv_bfloat16*)d_in[0], (const __nv_bfloat16*)d_in[3], (const __nv_bfloat16*)d_in[4],
        (const __nv_bfloat16*)d_in[6], (const __nv_bfloat16*)d_in[7], (const __nv_bfloat16*)d_in[8],
        (const __nv_bfloat16*)d_in[9], (__nv_bfloat16*)d_out);
}
```

```cpp
#include <cuda_runtime.h>
#include <cuda_bf16.h>
#include <cuda.h>
#include <stdint.h>

namespace {

constexpr int NB = 2, DM = 512, HQ = 32, HKV = 8, SK = 8192, DH = 128, FF = 1792;
constexpr int NCTA = 128, NSPLIT = 8, KEYS_PER_CTA = SK / NSPLIT;
constexpr int NWARP = 8, NTHREADS = NWARP * 32;
constexpr int NSTAGE = 3;
#define QTRIES (1 << 20)
#define QSLEEP 100
#define INIT_STAGES 1
constexpr int STAGE_BYTES = 8192;
constexpr int NBLK = KEYS_PER_CTA / (16 * NWARP);
constexpr int RING_BYTES = NWARP * NSTAGE * STAGE_BYTES;
constexpr int SMEM_BYTES = RING_BYTES + 4096 + 2048 + 1024;

__device__ unsigned long long g_q64[NB * HQ * DH / 2];
__device__ unsigned g_epoch;
__device__ unsigned long long g_pm[16 * NSPLIT * 4];
__device__ unsigned long long g_pl[16 * NSPLIT * 4];
__device__ unsigned long long g_po[16 * NSPLIT * 4 * DH];
__device__ float g_attn_acc[NB * DM];
__device__ float g_out_acc[4 * NB * DM];
__device__ unsigned g_bar;
__device__ unsigned g_done;

#define TS(i)
#define CTA_SYNC() asm volatile("bar.sync 1, 256;" ::: "memory")
__device__ __forceinline__ uint32_t smem_u32(const void* p) {
    return (uint32_t)__cvta_generic_to_shared(p);
}
__device__ __forceinline__ float bf16r(float x) {
    return __bfloat162float(__float2bfloat16_rn(x));
}
__device__ __forceinline__ uint32_t pack_bf16(float lo, float hi) {
    __nv_bfloat162 v = __floats2bfloat162_rn(lo, hi);
    return *reinterpret_cast<uint32_t*>(&v);
}
__device__ __forceinline__ float bf_lo(uint32_t v) { return __uint_as_float(v << 16); }
__device__ __forceinline__ float bf_hi(uint32_t v) { return __uint_as_float(v & 0xffff0000u); }

__device__ __forceinline__ void mbar_init(uint32_t bar, uint32_t cnt) {
    asm volatile("mbarrier.init.shared::cta.b64 [%0], %1;" ::"r"(bar), "r"(cnt) : "memory");
}
__device__ __forceinline__ void mbar_expect_tx(uint32_t bar, uint32_t bytes) {
    asm volatile("mbarrier.arrive.expect_tx.shared::cta.b64 _, [%0], %1;" ::"r"(bar), "r"(bytes) : "memory");
}
__device__ __forceinline__ void mbar_wait(uint32_t bar, uint32_t parity) {
    for (int i = 0; i < (1 << 22); i++) {
        uint32_t ok;
        asm volatile(
            "{\n"
            ".reg .pred p;\n"
            "mbarrier.try_wait.parity.shared::cta.b64 p, [%1], %2;\n"
            "selp.u32 %0, 1, 0, p;\n"
            "}\n" : "=r"(ok) : "r"(bar), "r"(parity) : "memory");
        if (ok) break;
    }
}
__device__ __forceinline__ void tma_2d(uint32_t dst, const CUtensorMap* map, uint32_t bar, int c0, int c1) {
    asm volatile(
        "cp.async.bulk.tensor.2d.shared::cluster.global.mbarrier::complete_tx::bytes [%0], [%1, {%3, %4}], [%2];"
        ::"r"(dst), "l"(map), "r"(bar), "r"(c0), "r"(c1) : "memory");
}
__device__ __forceinline__ void ldsm_x4(uint32_t addr, uint32_t& r0, uint32_t& r1, uint32_t& r2, uint32_t& r3) {
    asm volatile("ldmatrix.sync.aligned.m8n8.x4.shared.b16 {%0,%1,%2,%3}, [%4];"
                 : "=r"(r0), "=r"(r1), "=r"(r2), "=r"(r3) : "r"(addr) : "memory");
}
__device__ __forceinline__ void ldsm_x4_t(uint32_t addr, uint32_t& r0, uint32_t& r1, uint32_t& r2, uint32_t& r3) {
    asm volatile("ldmatrix.sync.aligned.m8n8.x4.trans.shared.b16 {%0,%1,%2,%3}, [%4];"
                 : "=r"(r0), "=r"(r1), "=r"(r2), "=r"(r3) : "r"(addr) : "memory");
}
__device__ __forceinline__ void mma16816(float* c, uint32_t a0, uint32_t a1, uint32_t a2, uint32_t a3,
                                         uint32_t b0, uint32_t b1) {
    asm volatile(
        "mma.sync.aligned.m16n8k16.row.col.f32.bf16.bf16.f32 {%0,%1,%2,%3}, {%4,%5,%6,%7}, {%8,%9}, {%0,%1,%2,%3};"
        : "+f"(c[0]), "+f"(c[1]), "+f"(c[2]), "+f"(c[3])
        : "r"(a0), "r"(a1), "r"(a2), "r"(a3), "r"(b0), "r"(b1));
}
__device__ __forceinline__ unsigned ld_acquire(const unsigned* p) {
    unsigned v;
    asm volatile("ld.acquire.gpu.global.u32 %0, [%1];" : "=r"(v) : "l"(p) : "memory");
    return v;
}
__device__ __forceinline__ uint4 ldg_nc_v4(const void* p) {
    uint4 v;
    asm volatile("ld.global.nc.L1::no_allocate.v4.u32 {%0,%1,%2,%3}, [%4];"
                 : "=r"(v.x), "=r"(v.y), "=r"(v.z), "=r"(v.w) : "l"(p));
    return v;
}
__device__ __forceinline__ uint32_t ldg_nc_u32(const void* p) {
    uint32_t v;
    asm volatile("ld.global.nc.L1::no_allocate.u32 %0, [%1];" : "=r"(v) : "l"(p));
    return v;
}

__device__ __forceinline__ void red_v4(float* p, float a, float b, float c, float d) {
    asm volatile("red.global.add.v4.f32 [%0], {%1,%2,%3,%4};" ::"l"(p), "f"(a), "f"(b), "f"(c), "f"(d) : "memory");
}

__device__ __forceinline__ void st_tag(unsigned long long* p, float v, unsigned tag) {
    unsigned long long w = ((unsigned long long)tag << 32) | __float_as_uint(v);
    asm volatile("st.relaxed.gpu.global.u64 [%0], %1;" ::"l"(p), "l"(w) : "memory");
}
__device__ __forceinline__ unsigned long long ld_tag(const unsigned long long* p) {
    unsigned long long w;
    asm volatile("ld.relaxed.gpu.global.u64 %0, [%1];" : "=l"(w) : "l"(p) : "memory");
    return w;
}

__device__ __forceinline__ void arrive_release(unsigned* ctr) {
    CTA_SYNC();
    if (threadIdx.x == 0) {
        asm volatile("fence.acq_rel.gpu;" ::: "memory");
        asm volatile("red.release.gpu.global.add.u32 [%0], 1;" ::"l"(ctr) : "memory");
    }
}
__device__ __forceinline__ void wait_count(unsigned* ctr, unsigned target) {
    if (threadIdx.x == 0) {
        unsigned iters = 0;
        while ((int)(ld_acquire(ctr) - target) < 0) {
            if (++iters > 2000000u) break;
        }
        asm volatile("fence.acq_rel.gpu;" ::: "memory");
    }
    CTA_SYNC();
}

__device__ __forceinline__ void layernorm_2x512(float* v, float* red, int tid) {
    int warp = tid >> 5, lane = tid & 31;
    float a0 = v[2 * tid], a1 = v[2 * tid + 1], b0 = v[512 + 2 * tid], b1 = v[512 + 2 * tid + 1];
    float sa = a0 + a1, sb = b0 + b1;
#pragma unroll
    for (int o = 16; o > 0; o >>= 1) {
        sa += __shfl_xor_sync(0xffffffffu, sa, o);
        sb += __shfl_xor_sync(0xffffffffu, sb, o);
    }
    if (lane == 0) { red[warp] = sa; red[8 + warp] = sb; }
    CTA_SYNC();
    float ma = 0.f, mb = 0.f;
#pragma unroll
    for (int w = 0; w < 8; w++) { ma += red[w]; mb += red[8 + w]; }
    ma *= (1.f / 512.f); mb *= (1.f / 512.f);
    float da0 = a0 - ma, da1 = a1 - ma, db0 = b0 - mb, db1 = b1 - mb;
    float va = da0 * da0 + da1 * da1, vb = db0 * db0 + db1 * db1;
#pragma unroll
    for (int o = 16; o > 0; o >>= 1) {
        va += __shfl_xor_sync(0xffffffffu, va, o);
        vb += __shfl_xor_sync(0xffffffffu, vb, o);
    }
    CTA_SYNC();
    if (lane == 0) { red[16 + warp] = va; red[24 + warp] = vb; }
    CTA_SYNC();
    va = 0.f; vb = 0.f;
#pragma unroll
    for (int w = 0; w < 8; w++) { va += red[16 + w]; vb += red[24 + w]; }
    va = bf16r(va * (1.f / 512.f)); vb = bf16r(vb * (1.f / 512.f));
    float mra = bf16r(ma), mrb = bf16r(mb);
    float sda = bf16r(sqrtf(bf16r(va + 1e-5f))), sdb = bf16r(sqrtf(bf16r(vb + 1e-5f)));
    v[2 * tid] = bf16r(bf16r(a0 - mra) / sda);
    v[2 * tid + 1] = bf16r(bf16r(a1 - mra) / sda);
    v[512 + 2 * tid] = bf16r(bf16r(b0 - mrb) / sdb);
    v[512 + 2 * tid + 1] = bf16r(bf16r(b1 - mrb) / sdb);
    CTA_SYNC();
}

__device__ __forceinline__ float gelu_tanh(float x) {
    const float k0 = 0.7978845608028654f, k1 = 0.044715f;
    float inner = k0 * (x + k1 * x * x * x);
    return 0.5f * x * (1.f + tanhf(inner));
}

__global__ void __launch_bounds__(NTHREADS, 1)
fused_kernel(const __grid_constant__ CUtensorMap mapK, const __grid_constant__ CUtensorMap mapV,
             const __nv_bfloat16* __restrict__ x, const __nv_bfloat16* __restrict__ wq,
             const __nv_bfloat16* __restrict__ wo, const __nv_bfloat16* __restrict__ w1,
             const __nv_bfloat16* __restrict__ b1, const __nv_bfloat16* __restrict__ w2,
             const __nv_bfloat16* __restrict__ b2, __nv_bfloat16* __restrict__ out) {
    extern __shared__ __align__(1024) uint8_t smem_raw[];
    uint8_t* smem = smem_raw + ((1024u - (smem_u32(smem_raw) & 1023u)) & 1023u);
    uint8_t* ring = smem;
    uint64_t* bars = reinterpret_cast<uint64_t*>(smem + RING_BYTES);
    float* s_vec = reinterpret_cast<float*>(smem + RING_BYTES + 256);
    float* s_red = reinterpret_cast<float*>(smem + RING_BYTES + 256 + 4096);
    float* s_o = s_red + 64;
    float* s_f = s_o + 64;

    const int tid = threadIdx.x, warp = tid >> 5, lane = tid & 31;
    const int cta = blockIdx.x;
    const int bh = cta >> 3, split = cta & 7;
    const int b = bh >> 3, kvh = bh & 7;

    TS(0);
    const uint32_t ring_w = smem_u32(ring) + warp * (NSTAGE * STAGE_BYTES);
    const uint32_t bar_w = smem_u32(bars) + warp * (NSTAGE * 8);
    if (lane == 0) {
#pragma unroll
        for (int s = 0; s < NSTAGE; s++) mbar_init(bar_w + s * 8, 1);
        asm volatile("fence.mbarrier_init.release.cluster;" ::: "memory");
    }
    __syncwarp();
    const unsigned epoch = __ldcg(&g_epoch) + 1u;
    uint32_t xv0 = ldg_nc_u32(x + 2 * tid);
    uint32_t xv1 = ldg_nc_u32(x + 512 + 2 * tid);
    uint4 wqv[8];
    {
        const __nv_bfloat16* p = wq + (size_t)(tid >> 2) * (HQ * DH) + cta * 32 + (tid & 3) * 8;
#pragma unroll
        for (int i = 0; i < 8; i++) wqv[i] = ldg_nc_v4(p + (size_t)i * 64 * (HQ * DH));
    }
    const int row0 = bh * SK + split * KEYS_PER_CTA + warp * 16;
    auto issue_stage = [&](int blk) {
        const int s = blk % NSTAGE;
        uint32_t dst = ring_w + s * STAGE_BYTES;
        uint32_t bar = bar_w + s * 8;
        int r = row0 + blk * 128;
        mbar_expect_tx(bar, STAGE_BYTES);
        tma_2d(dst, &mapK, bar, 0, r);
        tma_2d(dst + 2048, &mapK, bar, 64, r);
        tma_2d(dst + 4096, &mapV, bar, 0, r);
        tma_2d(dst + 6144, &mapV, bar, 64, r);
    };
    uint4 wov[8];
    uint4 w1v[4];
    uint4 w2v[4];
    const __nv_bfloat16* wo_p = wo + (size_t)((cta >> 2) * 128 + (tid >> 4)) * DM + (cta & 3) * 128 + (tid & 15) * 8;
    const int fcta = cta < 112 ? cta : 0;
    const __nv_bfloat16* w1_p = w1 + (size_t)(tid >> 1) * FF + fcta * 16 + (tid & 1) * 8;
    const float bias1 = __bfloat162float(b1[fcta * 16 + (tid & 15)]);
    const uint32_t bias2 = *reinterpret_cast<const uint32_t*>(b2 + 2 * tid);
    const __nv_bfloat16* w2_p = w2 + (size_t)(fcta * 16 + (tid >> 6)) * DM + (tid & 63) * 8;

    TS(1);
    s_vec[2 * tid] = bf_lo(xv0); s_vec[2 * tid + 1] = bf_hi(xv0);
    s_vec[512 + 2 * tid] = bf_lo(xv1); s_vec[512 + 2 * tid + 1] = bf_hi(xv1);
    CTA_SYNC();
    layernorm_2x512(s_vec, s_red, tid);

    {
        float acc[2][8];
#pragma unroll
        for (int i = 0; i < 8; i++) { acc[0][i] = 0.f; acc[1][i] = 0.f; }
#pragma unroll
        for (int i = 0; i < 8; i++) {
            int r = (tid >> 2) + i * 64;
            float x0 = s_vec[r], x1 = s_vec[512 + r];
            uint32_t w[4] = {wqv[i].x, wqv[i].y, wqv[i].z, wqv[i].w};
#pragma unroll
            for (int j = 0; j < 4; j++) {
                float lo = bf_lo(w[j]), hi = bf_hi(w[j]);
                acc[0][2 * j] += x0 * lo; acc[0][2 * j + 1] += x0 * hi;
                acc[1][2 * j] += x1 * lo; acc[1][2 * j + 1] += x1 * hi;
            }
        }
        if (lane == 0) {
#pragma unroll
            for (int s = 0; s < INIT_STAGES; s++) issue_stage(s);
        }
#pragma unroll
        for (int o = 4; o < 32; o <<= 1) {
#pragma unroll
            for (int i = 0; i < 8; i++) {
                acc[0][i] += __shfl_xor_sync(0xffffffffu, acc[0][i], o);
                acc[1][i] += __shfl_xor_sync(0xffffffffu, acc[1][i], o);
            }
        }
        __shared__ float s_qpart[NWARP][2][32];
        if (lane < 4) {
#pragma unroll
            for (int i = 0; i < 8; i++) {
                s_qpart[warp][0][lane * 8 + i] = acc[0][i];
                s_qpart[warp][1][lane * 8 + i] = acc[1][i];
            }
        }
        CTA_SYNC();
        if (tid < 32) {
            int bb = tid >> 4, c = (tid & 15) * 2;
            float s0 = 0.f, s1 = 0.f;
#pragma unroll
            for (int w = 0; w < NWARP; w++) { s0 += s_qpart[w][bb][c]; s1 += s_qpart[w][bb][c + 1]; }
            unsigned long long v = ((unsigned long long)epoch << 32) | pack_bf16(s0, s1);
            asm volatile("st.relaxed.gpu.global.u64 [%0], %1;" ::"l"(&g_q64[(bb * (HQ * DH) + cta * 32 + c) >> 1]), "l"(v) : "memory");
        }
    }
    TS(2);

    uint32_t qa[8][2];
    {
        __shared__ uint32_t s_qw[256];
        if (warp == 0) {
            const unsigned long long* qp = g_q64 + ((b * (HQ * DH) + kvh * 4 * DH) >> 1) + lane;
            uint32_t v[8];
            const uint32_t rw = smem_u32(ring) + (lane & 7) * (NSTAGE * STAGE_BYTES);
            const uint32_t bw = smem_u32(bars) + (lane & 7) * (NSTAGE * 8);
            const int r0 = bh * SK + split * KEYS_PER_CTA + (lane & 7) * 16;
            int nstg = INIT_STAGES;
            auto issue_other = [&](int st) {
                uint32_t dst = rw + st * STAGE_BYTES, bar = bw + st * 8;
                int r = r0 + st * 128;
                mbar_expect_tx(bar, STAGE_BYTES);
                tma_2d(dst, &mapK, bar, 0, r);
                tma_2d(dst + 2048, &mapK, bar, 64, r);
                tma_2d(dst + 4096, &mapV, bar, 0, r);
                tma_2d(dst + 6144, &mapV, bar, 64, r);
            };
            for (int tries = 0; tries < QTRIES; tries++) {
                bool ok = true;
#pragma unroll
                for (int i = 0; i < 8; i++) {
                    unsigned long long w = ld_tag(qp + i * 32);
                    ok = ok && ((unsigned)(w >> 32) == epoch);
                    v[i] = (uint32_t)w;
                }
                if (__all_sync(0xffffffffu, ok)) break;
                if (lane < NWARP && nstg < NSTAGE) {
                    uint32_t done;
                    asm volatile("{\n.reg .pred p;\nmbarrier.test_wait.parity.shared::cta.b64 p, [%1], 0;\nselp.u32 %0, 1, 0, p;\n}\n"
                                 : "=r"(done) : "r"(bw + (nstg - 1) * 8) : "memory");
                    if (done) { issue_other(nstg); nstg++; }
                }
                __nanosleep(QSLEEP);
            }
            if (lane < NWARP) for (; nstg < NSTAGE; nstg++) issue_other(nstg);
#pragma unroll
            for (int i = 0; i < 8; i++) s_qw[i * 32 + lane] = v[i];
        }
        CTA_SYNC();
        int hl = lane >> 2;
        const uint32_t* qs = s_qw + (hl & 3) * 64 + (lane & 3);
#pragma unroll
        for (int ks = 0; ks < 8; ks++) {
            qa[ks][0] = hl < 4 ? qs[ks * 8] : 0u;
            qa[ks][1] = hl < 4 ? qs[ks * 8 + 4] : 0u;
        }
    }
    TS(3);
    float oacc[16][4];
#pragma unroll
    for (int j = 0; j < 16; j++) { oacc[j][0] = 0.f; oacc[j][1] = 0.f; oacc[j][2] = 0.f; oacc[j][3] = 0.f; }
    float m_run = -INFINITY, l_run = 0.f;
    const float scale = 0.08838834764831845f;
    const float LOG2E = 1.4426950408889634f;

    const int lrow = lane & 7, lmat = lane >> 3;
    const int k_row = (lmat >> 1) * 8 + lrow;
    const int k_cofs = lmat & 1;
    const int v_row = (lmat & 1) * 8 + lrow;
    const int v_cofs = lmat >> 1;

#pragma unroll
    for (int it = 0; it < NBLK; it++) {
        wov[it] = ldg_nc_v4(wo_p + (size_t)it * 16 * DM);
        if (it < 4) w1v[it] = ldg_nc_v4(w1_p + (size_t)it * 128 * FF);
        else w2v[it - 4] = ldg_nc_v4(w2_p + (size_t)(it - 4) * 4 * DM);
        const int s = it % NSTAGE;
        const uint32_t parity = (it / NSTAGE) & 1;
        const uint32_t st = ring_w + s * STAGE_BYTES;
        mbar_wait(bar_w + s * 8, parity);

        float sc[2][4];
#pragma unroll
        for (int j = 0; j < 2; j++) { sc[j][0] = 0.f; sc[j][1] = 0.f; sc[j][2] = 0.f; sc[j][3] = 0.f; }
#pragma unroll
        for (int ks = 0; ks < 8; ks++) {
            int chunk = (ks & 3) * 2 + k_cofs;
            uint32_t addr = st + (ks >> 2) * 2048 + k_row * 128 + ((chunk ^ (k_row & 7)) << 4);
            uint32_t r0, r1, r2, r3;
            ldsm_x4(addr, r0, r1, r2, r3);
            mma16816(sc[0], qa[ks][0], 0u, qa[ks][1], 0u, r0, r1);
            mma16816(sc[1], qa[ks][0], 0u, qa[ks][1], 0u, r2, r3);
        }
        float v00 = bf16r(bf16r(sc[0][0]) * scale), v01 = bf16r(bf16r(sc[0][1]) * scale);
        float v10 = bf16r(bf16r(sc[1][0]) * scale), v11 = bf16r(bf16r(sc[1][1]) * scale);
        float mx = fmaxf(fmaxf(v00, v01), fmaxf(v10, v11));
        mx = fmaxf(mx, __shfl_xor_sync(0xffffffffu, mx, 1));
        mx = fmaxf(mx, __shfl_xor_sync(0xffffffffu, mx, 2));
        float m_new = fmaxf(m_run, mx);
        float corr = exp2f((m_run - m_new) * LOG2E);
        float p00 = exp2f((v00 - m_new) * LOG2E), p01 = exp2f((v01 - m_new) * LOG2E);
        float p10 = exp2f((v10 - m_new) * LOG2E), p11 = exp2f((v11 - m_new) * LOG2E);
        l_run = l_run * corr + (p00 + p01 + p10 + p11);
        m_run = m_new;
        uint32_t pa0 = pack_bf16(p00, p01), pa2 = pack_bf16(p10, p11);
#pragma unroll
        for (int j = 0; j < 16; j++) { oacc[j][0] *= corr; oacc[j][1] *= corr; }
#pragma unroll
        for (int jj = 0; jj < 8; jj++) {
            int chunk = (jj & 3) * 2 + v_cofs;
            uint32_t addr = st + 4096 + (jj >> 2) * 2048 + v_row * 128 + ((chunk ^ (v_row & 7)) << 4);
            uint32_t r0, r1, r2, r3;
            ldsm_x4_t(addr, r0, r1, r2, r3);
            mma16816(oacc[2 * jj], pa0, 0u, pa2, 0u, r0, r1);
            mma16816(oacc[2 * jj + 1], pa0, 0u, pa2, 0u, r2, r3);
        }
        __syncwarp();
        if (lane == 0 && it + NSTAGE < NBLK) issue_stage(it + NSTAGE);
    }
    TS(4);
    l_run += __shfl_xor_sync(0xffffffffu, l_run, 1);
    l_run += __shfl_xor_sync(0xffffffffu, l_run, 2);

    CTA_SYNC();
    float* r_o = reinterpret_cast<float*>(ring);
    float* r_m = reinterpret_cast<float*>(ring + 16384);
    float* r_l = r_m + 32;
    if (lane < 16) {
        int hl = lane >> 2;
#pragma unroll
        for (int j = 0; j < 16; j++) {
            float2 v = make_float2(oacc[j][0], oacc[j][1]);
            *reinterpret_cast<float2*>(&r_o[(warp * 4 + hl) * DH + j * 8 + (lane & 3) * 2]) = v;
        }
        if ((lane & 3) == 0) { r_m[warp * 4 + hl] = m_run; r_l[warp * 4 + hl] = l_run; }
    }
    CTA_SYNC();
    {
        int hl = tid >> 6, d = (tid & 63) * 2;
        float mm = -INFINITY;
#pragma unroll
        for (int w = 0; w < NWARP; w++) mm = fmaxf(mm, r_m[w * 4 + hl]);
        float o0 = 0.f, o1 = 0.f, ll = 0.f;
#pragma unroll
        for (int w = 0; w < NWARP; w++) {
            float c = exp2f((r_m[w * 4 + hl] - mm) * LOG2E);
            float2 v = *reinterpret_cast<float2*>(&r_o[(w * 4 + hl) * DH + d]);
            o0 += c * v.x; o1 += c * v.y; ll += c * r_l[w * 4 + hl];
        }
        int pidx = (cta * 4 + hl);
        st_tag(&g_po[(size_t)pidx * DH + d], o0, epoch);
        st_tag(&g_po[(size_t)pidx * DH + d + 1], o1, epoch);
        if ((tid & 63) == 0) { st_tag(&g_pm[pidx], mm, epoch); st_tag(&g_pl[pidx], ll, epoch); }
    }
    TS(5);

    {
        int head = cta >> 2;
        int kv = head >> 2, hl = head & 3;
        {
            int bb = tid >> 7, d = tid & 127;
            int base = ((bb * 8 + kv) * NSPLIT) * 4 + hl;
            float pm[NSPLIT], pl[NSPLIT], po[NSPLIT];
            for (int tries = 0; tries < (1 << 20); tries++) {
                bool ok = true;
#pragma unroll
                for (int s = 0; s < NSPLIT; s++) {
                    unsigned long long a0 = ld_tag(&g_pm[base + s * 4]);
                    unsigned long long a1 = ld_tag(&g_pl[base + s * 4]);
                    unsigned long long a2 = ld_tag(&g_po[(size_t)(base + s * 4) * DH + d]);
                    ok = ok && ((unsigned)(a0 >> 32) == epoch) && ((unsigned)(a1 >> 32) == epoch) && ((unsigned)(a2 >> 32) == epoch);
                    pm[s] = __uint_as_float((unsigned)a0); pl[s] = __uint_as_float((unsigned)a1); po[s] = __uint_as_float((unsigned)a2);
                }
                if (ok) break;
                __nanosleep(64);
            }
            TS(6);
            float mm = -INFINITY;
#pragma unroll
            for (int s = 0; s < NSPLIT; s++) mm = fmaxf(mm, pm[s]);
            float oo = 0.f, ll = 0.f;
#pragma unroll
            for (int s = 0; s < NSPLIT; s++) {
                float c = exp2f((pm[s] - mm) * LOG2E);
                oo += c * po[s]; ll += c * pl[s];
            }
            s_vec[tid] = bf16r(oo / ll);
        }
        CTA_SYNC();
        float a[2][8];
#pragma unroll
        for (int j = 0; j < 8; j++) { a[0][j] = 0.f; a[1][j] = 0.f; }
#pragma unroll
        for (int i = 0; i < 8; i++) {
            int r = (tid >> 4) + 16 * i;
            float o0 = s_vec[r], o1 = s_vec[128 + r];
            uint32_t w[4] = {wov[i].x, wov[i].y, wov[i].z, wov[i].w};
#pragma unroll
            for (int j = 0; j < 4; j++) {
                float lo = bf_lo(w[j]), hi = bf_hi(w[j]);
                a[0][2 * j] += o0 * lo; a[0][2 * j + 1] += o0 * hi;
                a[1][2 * j] += o1 * lo; a[1][2 * j + 1] += o1 * hi;
            }
        }
#pragma unroll
        for (int j = 0; j < 8; j++) {
            a[0][j] += __shfl_xor_sync(0xffffffffu, a[0][j], 16);
            a[1][j] += __shfl_xor_sync(0xffffffffu, a[1][j], 16);
        }
        float* s_p = reinterpret_cast<float*>(ring);
        if (lane < 16) {
#pragma unroll
            for (int bb = 0; bb < 2; bb++) {
                float4* dst = reinterpret_cast<float4*>(&s_p[(warp * 2 + bb) * 128 + lane * 8]);
                dst[0] = make_float4(a[bb][0], a[bb][1], a[bb][2], a[bb][3]);
                dst[1] = make_float4(a[bb][4], a[bb][5], a[bb][6], a[bb][7]);
            }
        }
        CTA_SYNC();
        if (tid < 64) {
            int bb = tid >> 5, c4 = (tid & 31) * 4;
            float4 acc = make_float4(0.f, 0.f, 0.f, 0.f);
#pragma unroll
            for (int w = 0; w < NWARP; w++) {
                float4 v = *reinterpret_cast<float4*>(&s_p[(w * 2 + bb) * 128 + c4]);
                acc.x += v.x; acc.y += v.y; acc.z += v.z; acc.w += v.w;
            }
            red_v4(&g_attn_acc[bb * 512 + (cta & 3) * 128 + c4], acc.x, acc.y, acc.z, acc.w);
        }
    }
    TS(7);
    arrive_release(&g_bar);
    if (cta >= 112 && cta != NCTA - 1) return;
    wait_count(&g_bar, epoch * NCTA);
    TS(8);

    float h00, h01, h10, h11;
    {
        float2 aa = __ldcg(reinterpret_cast<const float2*>(&g_attn_acc[2 * tid]));
        float2 ab = __ldcg(reinterpret_cast<const float2*>(&g_attn_acc[512 + 2 * tid]));
        h00 = bf16r(bf_lo(xv0) + bf16r(aa.x)); h01 = bf16r(bf_hi(xv0) + bf16r(aa.y));
        h10 = bf16r(bf_lo(xv1) + bf16r(ab.x)); h11 = bf16r(bf_hi(xv1) + bf16r(ab.y));
        s_vec[2 * tid] = h00; s_vec[2 * tid + 1] = h01;
        s_vec[512 + 2 * tid] = h10; s_vec[512 + 2 * tid + 1] = h11;
        CTA_SYNC();
        layernorm_2x512(s_vec, s_red, tid);
        if (cta < 112) {
            float f[2][8];
#pragma unroll
            for (int j = 0; j < 8; j++) { f[0][j] = 0.f; f[1][j] = 0.f; }
#pragma unroll
            for (int i = 0; i < 4; i++) {
                int r = (tid >> 1) + 128 * i;
                float n0 = s_vec[r], n1 = s_vec[512 + r];
                uint32_t w[4] = {w1v[i].x, w1v[i].y, w1v[i].z, w1v[i].w};
#pragma unroll
                for (int j = 0; j < 4; j++) {
                    float lo = bf_lo(w[j]), hi = bf_hi(w[j]);
                    f[0][2 * j] += n0 * lo; f[0][2 * j + 1] += n0 * hi;
                    f[1][2 * j] += n1 * lo; f[1][2 * j + 1] += n1 * hi;
                }
            }
#pragma unroll
            for (int o = 2; o < 32; o <<= 1) {
#pragma unroll
                for (int j = 0; j < 8; j++) {
                    f[0][j] += __shfl_xor_sync(0xffffffffu, f[0][j], o);
                    f[1][j] += __shfl_xor_sync(0xffffffffu, f[1][j], o);
                }
            }
            float* s_fp = reinterpret_cast<float*>(ring);
            if (lane < 2) {
#pragma unroll
                for (int j = 0; j < 8; j++) {
                    s_fp[(warp * 2 + 0) * 16 + lane * 8 + j] = f[0][j];
                    s_fp[(warp * 2 + 1) * 16 + lane * 8 + j] = f[1][j];
                }
            }
            CTA_SYNC();
            if (tid < 32) {
                int bb = tid >> 4, c = tid & 15;
                float sacc = 0.f;
#pragma unroll
                for (int w = 0; w < NWARP; w++) sacc += s_fp[(w * 2 + bb) * 16 + c];
                float hh = bf16r(bf16r(sacc) + bias1);
                s_f[tid] = bf16r(gelu_tanh(hh));
            }
            CTA_SYNC();
            float a[2][8];
#pragma unroll
            for (int j = 0; j < 8; j++) { a[0][j] = 0.f; a[1][j] = 0.f; }
#pragma unroll
            for (int i = 0; i < 4; i++) {
                int r = (tid >> 6) + 4 * i;
                float f0 = s_f[r], f1 = s_f[16 + r];
                uint32_t w[4] = {w2v[i].x, w2v[i].y, w2v[i].z, w2v[i].w};
#pragma unroll
                for (int j = 0; j < 4; j++) {
                    float lo = bf_lo(w[j]), hi = bf_hi(w[j]);
                    a[0][2 * j] += f0 * lo; a[0][2 * j + 1] += f0 * hi;
                    a[1][2 * j] += f1 * lo; a[1][2 * j + 1] += f1 * hi;
                }
            }
            float* s_p = reinterpret_cast<float*>(ring) + 1024;
            {
                int g = tid >> 6, c8 = (tid & 63) * 8;
#pragma unroll
                for (int bb = 0; bb < 2; bb++) {
                    float4* dst = reinterpret_cast<float4*>(&s_p[(g * 2 + bb) * 512 + c8]);
                    dst[0] = make_float4(a[bb][0], a[bb][1], a[bb][2], a[bb][3]);
                    dst[1] = make_float4(a[bb][4], a[bb][5], a[bb][6], a[bb][7]);
                }
            }
            CTA_SYNC();
            {
                int bb = tid >> 7, c4 = (tid & 127) * 4;
                float4 acc = make_float4(0.f, 0.f, 0.f, 0.f);
#pragma unroll
                for (int g = 0; g < 4; g++) {
                    float4 v = *reinterpret_cast<float4*>(&s_p[(g * 2 + bb) * 512 + c4]);
                    acc.x += v.x; acc.y += v.y; acc.z += v.z; acc.w += v.w;
                }
                red_v4(&g_out_acc[(cta & 3) * 1024 + bb * 512 + c4], acc.x, acc.y, acc.z, acc.w);
            }
        }
    }
    TS(9);
    if (cta < 112) {
        arrive_release(&g_done);
    }
    if (cta == NCTA - 1) {
        wait_count(&g_done, epoch * 112u);
        float2 oa = make_float2(0.f, 0.f), ob = make_float2(0.f, 0.f);
#pragma unroll
        for (int c = 0; c < 4; c++) {
            float2 va = __ldcg(reinterpret_cast<const float2*>(&g_out_acc[c * 1024 + 2 * tid]));
            float2 vb = __ldcg(reinterpret_cast<const float2*>(&g_out_acc[c * 1024 + 512 + 2 * tid]));
            oa.x += va.x; oa.y += va.y; ob.x += vb.x; ob.y += vb.y;
        }
        uint32_t bb = bias2;
        float bl = bf_lo(bb), bhh = bf_hi(bb);
        float r00 = h00 + bf16r(bf16r(oa.x) + bl), r01 = h01 + bf16r(bf16r(oa.y) + bhh);
        float r10 = h10 + bf16r(bf16r(ob.x) + bl), r11 = h11 + bf16r(bf16r(ob.y) + bhh);
        *reinterpret_cast<uint32_t*>(out + 2 * tid) = pack_bf16(r00, r01);
        *reinterpret_cast<uint32_t*>(out + 512 + 2 * tid) = pack_bf16(r10, r11);
        for (int i = tid; i < NB * DM; i += NTHREADS) g_attn_acc[i] = 0.f;
        for (int i = tid; i < 4 * NB * DM; i += NTHREADS) g_out_acc[i] = 0.f;
        if (tid == 0) g_epoch = epoch;
    }
    TS(10);
}

typedef CUresult (*PFN_encodeTiled)(CUtensorMap*, CUtensorMapDataType, cuuint32_t, void*, const cuuint64_t*,
                                    const cuuint64_t*, const cuuint32_t*, const cuuint32_t*, CUtensorMapInterleave,
                                    CUtensorMapSwizzle, CUtensorMapL2promotion, CUtensorMapFloatOOBfill);

}

extern "C" void kernel_launch(void* const* d_in, const int* in_sizes, int n_in, void* d_out, int out_size) {
    static PFN_encodeTiled enc = nullptr;
    if (!enc) {
        void* fn = nullptr;
        cudaDriverEntryPointQueryResult qres;
        cudaGetDriverEntryPoint("cuTensorMapEncodeTiled", &fn, cudaEnableDefault, &qres);
        enc = (PFN_encodeTiled)fn;
        cudaFuncSetAttribute(fused_kernel, cudaFuncAttributeMaxDynamicSharedMemorySize, SMEM_BYTES);
    }
    CUtensorMap mapK, mapV;
    cuuint64_t gdim[2] = {(cuuint64_t)DH, (cuuint64_t)NB * HKV * SK};
    cuuint64_t gstr[1] = {(cuuint64_t)DH * 2};
    cuuint32_t box[2] = {64, 16};
    cuuint32_t estr[2] = {1, 1};
    enc(&mapK, CU_TENSOR_MAP_DATA_TYPE_BFLOAT16, 2, d_in[1], gdim, gstr, box, estr, CU_TENSOR_MAP_INTERLEAVE_NONE,
        CU_TENSOR_MAP_SWIZZLE_128B, CU_TENSOR_MAP_L2_PROMOTION_L2_128B, CU_TENSOR_MAP_FLOAT_OOB_FILL_NONE);
    enc(&mapV, CU_TENSOR_MAP_DATA_TYPE_BFLOAT16, 2, d_in[2], gdim, gstr, box, estr, CU_TENSOR_MAP_INTERLEAVE_NONE,
        CU_TENSOR_MAP_SWIZZLE_128B, CU_TENSOR_MAP_L2_PROMOTION_L2_128B, CU_TENSOR_MAP_FLOAT_OOB_FILL_NONE);
    fused_kernel<<<NCTA, NTHREADS, SMEM_BYTES>>>(
        mapK, mapV, (const __nv_bfloat16*)d_in[0], (const __nv_bfloat16*)d_in[3], (const __nv_bfloat16*)d_in[4],
        (const __nv_bfloat16*)d_in[6], (const __nv_bfloat16*)d_in[7], (const __nv_bfloat16*)d_in[8],
        (const __nv_bfloat16*)d_in[9], (__nv_bfloat16*)d_out);
}
```

```cpp
#include <cuda_runtime.h>
#include <cuda_bf16.h>
#include <cuda.h>
#include <stdint.h>

namespace {

constexpr int NB = 2, DM = 512, HQ = 32, HKV = 8, SK = 8192, DH = 128, FF = 1792;
constexpr int NCTA = 128, NSPLIT = 8, KEYS_PER_CTA = SK / NSPLIT;
constexpr int NWARP = 8, NTHREADS = NWARP * 32;
constexpr int NSTAGE = 3;
#define QTRIES (1 << 20)
#define QSLEEP 100
#define INIT_STAGES 1
constexpr int STAGE_BYTES = 8192;
constexpr int NBLK = KEYS_PER_CTA / (16 * NWARP);
constexpr int RING_BYTES = NWARP * NSTAGE * STAGE_BYTES;
constexpr int SMEM_BYTES = RING_BYTES + 4096 + 2048 + 1024;

__device__ unsigned long long g_q64[NB * HQ * DH / 2];
__device__ unsigned g_epoch;
__device__ unsigned long long g_pm[16 * NSPLIT * 4];
__device__ unsigned long long g_pl[16 * NSPLIT * 4];
__device__ unsigned long long g_po[16 * NSPLIT * 4 * DH];
__device__ float g_attn_acc[NB * DM];
__device__ float g_out_acc[4 * NB * DM];
__device__ unsigned g_bar;
__device__ unsigned g_done;

#define TS(i)
#define CTA_SYNC() asm volatile("bar.sync 1, 256;" ::: "memory")
__device__ __forceinline__ uint32_t smem_u32(const void* p) {
    return (uint32_t)__cvta_generic_to_shared(p);
}
__device__ __forceinline__ float bf16r(float x) {
    return __bfloat162float(__float2bfloat16_rn(x));
}
__device__ __forceinline__ uint32_t pack_bf16(float lo, float hi) {
    __nv_bfloat162 v = __floats2bfloat162_rn(lo, hi);
    return *reinterpret_cast<uint32_t*>(&v);
}
__device__ __forceinline__ float bf_lo(uint32_t v) { return __uint_as_float(v << 16); }
__device__ __forceinline__ float bf_hi(uint32_t v) { return __uint_as_float(v & 0xffff0000u); }

__device__ __forceinline__ void mbar_init(uint32_t bar, uint32_t cnt) {
    asm volatile("mbarrier.init.shared::cta.b64 [%0], %1;" ::"r"(bar), "r"(cnt) : "memory");
}
__device__ __forceinline__ void mbar_expect_tx(uint32_t bar, uint32_t bytes) {
    asm volatile("mbarrier.arrive.expect_tx.shared::cta.b64 _, [%0], %1;" ::"r"(bar), "r"(bytes) : "memory");
}
__device__ __forceinline__ void mbar_wait(uint32_t bar, uint32_t parity) {
    for (int i = 0; i < (1 << 22); i++) {
        uint32_t ok;
        asm volatile(
            "{\n"
            ".reg .pred p;\n"
            "mbarrier.try_wait.parity.shared::cta.b64 p, [%1], %2;\n"
            "selp.u32 %0, 1, 0, p;\n"
            "}\n" : "=r"(ok) : "r"(bar), "r"(parity) : "memory");
        if (ok) break;
    }
}
__device__ __forceinline__ void tma_2d(uint32_t dst, const CUtensorMap* map, uint32_t bar, int c0, int c1) {
    asm volatile(
        "cp.async.bulk.tensor.2d.shared::cluster.global.mbarrier::complete_tx::bytes [%0], [%1, {%3, %4}], [%2];"
        ::"r"(dst), "l"(map), "r"(bar), "r"(c0), "r"(c1) : "memory");
}
__device__ __forceinline__ void ldsm_x4(uint32_t addr, uint32_t& r0, uint32_t& r1, uint32_t& r2, uint32_t& r3) {
    asm volatile("ldmatrix.sync.aligned.m8n8.x4.shared.b16 {%0,%1,%2,%3}, [%4];"
                 : "=r"(r0), "=r"(r1), "=r"(r2), "=r"(r3) : "r"(addr) : "memory");
}
__device__ __forceinline__ void ldsm_x4_t(uint32_t addr, uint32_t& r0, uint32_t& r1, uint32_t& r2, uint32_t& r3) {
    asm volatile("ldmatrix.sync.aligned.m8n8.x4.trans.shared.b16 {%0,%1,%2,%3}, [%4];"
                 : "=r"(r0), "=r"(r1), "=r"(r2), "=r"(r3) : "r"(addr) : "memory");
}
__device__ __forceinline__ void mma16816(float* c, uint32_t a0, uint32_t a1, uint32_t a2, uint32_t a3,
                                         uint32_t b0, uint32_t b1) {
    asm volatile(
        "mma.sync.aligned.m16n8k16.row.col.f32.bf16.bf16.f32 {%0,%1,%2,%3}, {%4,%5,%6,%7}, {%8,%9}, {%0,%1,%2,%3};"
        : "+f"(c[0]), "+f"(c[1]), "+f"(c[2]), "+f"(c[3])
        : "r"(a0), "r"(a1), "r"(a2), "r"(a3), "r"(b0), "r"(b1));
}
__device__ __forceinline__ unsigned ld_acquire(const unsigned* p) {
    unsigned v;
    asm volatile("ld.acquire.gpu.global.u32 %0, [%1];" : "=r"(v) : "l"(p) : "memory");
    return v;
}
__device__ __forceinline__ uint4 ldg_nc_v4(const void* p) {
    uint4 v;
    asm volatile("ld.global.nc.L1::no_allocate.v4.u32 {%0,%1,%2,%3}, [%4];"
                 : "=r"(v.x), "=r"(v.y), "=r"(v.z), "=r"(v.w) : "l"(p));
    return v;
}
__device__ __forceinline__ uint32_t ldg_nc_u32(const void* p) {
    uint32_t v;
    asm volatile("ld.global.nc.L1::no_allocate.u32 %0, [%1];" : "=r"(v) : "l"(p));
    return v;
}

__device__ __forceinline__ void red_v4(float* p, float a, float b, float c, float d) {
    asm volatile("red.global.add.v4.f32 [%0], {%1,%2,%3,%4};" ::"l"(p), "f"(a), "f"(b), "f"(c), "f"(d) : "memory");
}

__device__ __forceinline__ void st_tag(unsigned long long* p, float v, unsigned tag) {
    unsigned long long w = ((unsigned long long)tag << 32) | __float_as_uint(v);
    asm volatile("st.relaxed.gpu.global.u64 [%0], %1;" ::"l"(p), "l"(w) : "memory");
}
__device__ __forceinline__ unsigned long long ld_tag(const unsigned long long* p) {
    unsigned long long w;
    asm volatile("ld.relaxed.gpu.global.u64 %0, [%1];" : "=l"(w) : "l"(p) : "memory");
    return w;
}

__device__ __forceinline__ void grid_barrier() {
    CTA_SYNC();
    if (threadIdx.x == 0) {
        __threadfence();
        unsigned old = atomicAdd(&g_bar, 1u);
        unsigned target = (old / NCTA + 1u) * NCTA;
        unsigned iters = 0;
        while ((int)(ld_acquire(&g_bar) - target) < 0) {
            if (++iters > 2000000u) break;
        }
        __threadfence();
    }
    CTA_SYNC();
}

__device__ __forceinline__ void layernorm_2x512(float* v, float* red, int tid) {
    int warp = tid >> 5, lane = tid & 31;
    float a0 = v[2 * tid], a1 = v[2 * tid + 1], b0 = v[512 + 2 * tid], b1 = v[512 + 2 * tid + 1];
    float sa = a0 + a1, sb = b0 + b1;
#pragma unroll
    for (int o = 16; o > 0; o >>= 1) {
        sa += __shfl_xor_sync(0xffffffffu, sa, o);
        sb += __shfl_xor_sync(0xffffffffu, sb, o);
    }
    if (lane == 0) { red[warp] = sa; red[8 + warp] = sb; }
    CTA_SYNC();
    float ma = 0.f, mb = 0.f;
#pragma unroll
    for (int w = 0; w < 8; w++) { ma += red[w]; mb += red[8 + w]; }
    ma *= (1.f / 512.f); mb *= (1.f / 512.f);
    float da0 = a0 - ma, da1 = a1 - ma, db0 = b0 - mb, db1 = b1 - mb;
    float va = da0 * da0 + da1 * da1, vb = db0 * db0 + db1 * db1;
#pragma unroll
    for (int o = 16; o > 0; o >>= 1) {
        va += __shfl_xor_sync(0xffffffffu, va, o);
        vb += __shfl_xor_sync(0xffffffffu, vb, o);
    }
    CTA_SYNC();
    if (lane == 0) { red[16 + warp] = va; red[24 + warp] = vb; }
    CTA_SYNC();
    va = 0.f; vb = 0.f;
#pragma unroll
    for (int w = 0; w < 8; w++) { va += red[16 + w]; vb += red[24 + w]; }
    va = bf16r(va * (1.f / 512.f)); vb = bf16r(vb * (1.f / 512.f));
    float mra = bf16r(ma), mrb = bf16r(mb);
    float sda = bf16r(sqrtf(bf16r(va + 1e-5f))), sdb = bf16r(sqrtf(bf16r(vb + 1e-5f)));
    v[2 * tid] = bf16r(bf16r(a0 - mra) / sda);
    v[2 * tid + 1] = bf16r(bf16r(a1 - mra) / sda);
    v[512 + 2 * tid] = bf16r(bf16r(b0 - mrb) / sdb);
    v[512 + 2 * tid + 1] = bf16r(bf16r(b1 - mrb) / sdb);
    CTA_SYNC();
}

__device__ __forceinline__ float gelu_tanh(float x) {
    const float k0 = 0.7978845608028654f, k1 = 0.044715f;
    float inner = k0 * (x + k1 * x * x * x);
    return 0.5f * x * (1.f + tanhf(inner));
}

__global__ void __launch_bounds__(NTHREADS, 1)
fused_kernel(const __grid_constant__ CUtensorMap mapK, const __grid_constant__ CUtensorMap mapV,
             const __nv_bfloat16* __restrict__ x, const __nv_bfloat16* __restrict__ wq,
             const __nv_bfloat16* __restrict__ wo, const __nv_bfloat16* __restrict__ w1,
             const __nv_bfloat16* __restrict__ b1, const __nv_bfloat16* __restrict__ w2,
             const __nv_bfloat16* __restrict__ b2, __nv_bfloat16* __restrict__ out) {
    extern __shared__ __align__(1024) uint8_t smem_raw[];
    uint8_t* smem = smem_raw + ((1024u - (smem_u32(smem_raw) & 1023u)) & 1023u);
    uint8_t* ring = smem;
    uint64_t* bars = reinterpret_cast<uint64_t*>(smem + RING_BYTES);
    float* s_vec = reinterpret_cast<float*>(smem + RING_BYTES + 256);
    float* s_red = reinterpret_cast<float*>(smem + RING_BYTES + 256 + 4096);
    float* s_o = s_red + 64;
    float* s_f = s_o + 64;

    const int tid = threadIdx.x, warp = tid >> 5, lane = tid & 31;
    const int cta = blockIdx.x;
    const int bh = cta >> 3, split = cta & 7;
    const int b = bh >> 3, kvh = bh & 7;

    TS(0);
    const uint32_t ring_w = smem_u32(ring) + warp * (NSTAGE * STAGE_BYTES);
    const uint32_t bar_w = smem_u32(bars) + warp * (NSTAGE * 8);
    if (lane == 0) {
#pragma unroll
        for (int s = 0; s < NSTAGE; s++) mbar_init(bar_w + s * 8, 1);
        asm volatile("fence.mbarrier_init.release.cluster;" ::: "memory");
    }
    __syncwarp();
    const unsigned epoch = __ldcg(&g_epoch) + 1u;
    uint32_t xv0 = ldg_nc_u32(x + 2 * tid);
    uint32_t xv1 = ldg_nc_u32(x + 512 + 2 * tid);
    uint4 wqv[8];
    {
        const __nv_bfloat16* p = wq + (size_t)(tid >> 2) * (HQ * DH) + cta * 32 + (tid & 3) * 8;
#pragma unroll
        for (int i = 0; i < 8; i++) wqv[i] = ldg_nc_v4(p + (size_t)i * 64 * (HQ * DH));
    }
    const int row0 = bh * SK + split * KEYS_PER_CTA + warp * 16;
    auto issue_stage = [&](int blk) {
        const int s = blk % NSTAGE;
        uint32_t dst = ring_w + s * STAGE_BYTES;
        uint32_t bar = bar_w + s * 8;
        int r = row0 + blk * 128;
        mbar_expect_tx(bar, STAGE_BYTES);
        tma_2d(dst, &mapK, bar, 0, r);
        tma_2d(dst + 2048, &mapK, bar, 64, r);
        tma_2d(dst + 4096, &mapV, bar, 0, r);
        tma_2d(dst + 6144, &mapV, bar, 64, r);
    };
    uint4 wov[8];
    uint4 w1v[4];
    uint4 w2v[4];
    const __nv_bfloat16* wo_p = wo + (size_t)((cta >> 2) * 128 + (tid >> 4)) * DM + (cta & 3) * 128 + (tid & 15) * 8;
    const int fcta = cta < 112 ? cta : 0;
    const __nv_bfloat16* w1_p = w1 + (size_t)(tid >> 1) * FF + fcta * 16 + (tid & 1) * 8;
    const float bias1 = __bfloat162float(b1[fcta * 16 + (tid & 15)]);
    const uint32_t bias2 = *reinterpret_cast<const uint32_t*>(b2 + 2 * tid);
    const __nv_bfloat16* w2_p = w2 + (size_t)(fcta * 16 + (tid >> 6)) * DM + (tid & 63) * 8;

    TS(1);
    s_vec[2 * tid] = bf_lo(xv0); s_vec[2 * tid + 1] = bf_hi(xv0);
    s_vec[512 + 2 * tid] = bf_lo(xv1); s_vec[512 + 2 * tid + 1] = bf_hi(xv1);
    CTA_SYNC();
    layernorm_2x512(s_vec, s_red, tid);

    {
        float acc[2][8];
#pragma unroll
        for (int i = 0; i < 8; i++) { acc[0][i] = 0.f; acc[1][i] = 0.f; }
#pragma unroll
        for (int i = 0; i < 8; i++) {
            int r = (tid >> 2) + i * 64;
            float x0 = s_vec[r], x1 = s_vec[512 + r];
            uint32_t w[4] = {wqv[i].x, wqv[i].y, wqv[i].z, wqv[i].w};
#pragma unroll
            for (int j = 0; j < 4; j++) {
                float lo = bf_lo(w[j]), hi = bf_hi(w[j]);
                acc[0][2 * j] += x0 * lo; acc[0][2 * j + 1] += x0 * hi;
                acc[1][2 * j] += x1 * lo; acc[1][2 * j + 1] += x1 * hi;
            }
        }
        if (lane == 0) {
#pragma unroll
            for (int s = 0; s < INIT_STAGES; s++) issue_stage(s);
        }
#pragma unroll
        for (int o = 4; o < 32; o <<= 1) {
#pragma unroll
            for (int i = 0; i < 8; i++) {
                acc[0][i] += __shfl_xor_sync(0xffffffffu, acc[0][i], o);
                acc[1][i] += __shfl_xor_sync(0xffffffffu, acc[1][i], o);
            }
        }
        __shared__ float s_qpart[NWARP][2][32];
        if (lane < 4) {
#pragma unroll
            for (int i = 0; i < 8; i++) {
                s_qpart[warp][0][lane * 8 + i] = acc[0][i];
                s_qpart[warp][1][lane * 8 + i] = acc[1][i];
            }
        }
        CTA_SYNC();
        if (tid < 32) {
            int bb = tid >> 4, c = (tid & 15) * 2;
            float s0 = 0.f, s1 = 0.f;
#pragma unroll
            for (int w = 0; w < NWARP; w++) { s0 += s_qpart[w][bb][c]; s1 += s_qpart[w][bb][c + 1]; }
            unsigned long long v = ((unsigned long long)epoch << 32) | pack_bf16(s0, s1);
            asm volatile("st.relaxed.gpu.global.u64 [%0], %1;" ::"l"(&g_q64[(bb * (HQ * DH) + cta * 32 + c) >> 1]), "l"(v) : "memory");
        }
    }
    TS(2);

    uint32_t qa[8][2];
    {
        __shared__ uint32_t s_qw[256];
        if (warp == 0) {
            const unsigned long long* qp = g_q64 + ((b * (HQ * DH) + kvh * 4 * DH) >> 1) + lane;
            uint32_t v[8];
            const uint32_t rw = smem_u32(ring) + (lane & 7) * (NSTAGE * STAGE_BYTES);
            const uint32_t bw = smem_u32(bars) + (lane & 7) * (NSTAGE * 8);
            const int r0 = bh * SK + split * KEYS_PER_CTA + (lane & 7) * 16;
            int nstg = INIT_STAGES;
            auto issue_other = [&](int st) {
                uint32_t dst = rw + st * STAGE_BYTES, bar = bw + st * 8;
                int r = r0 + st * 128;
                mbar_expect_tx(bar, STAGE_BYTES);
                tma_2d(dst, &mapK, bar, 0, r);
                tma_2d(dst + 2048, &mapK, bar, 64, r);
                tma_2d(dst + 4096, &mapV, bar, 0, r);
                tma_2d(dst + 6144, &mapV, bar, 64, r);
            };
            for (int tries = 0; tries < QTRIES; tries++) {
                bool ok = true;
#pragma unroll
                for (int i = 0; i < 8; i++) {
                    unsigned long long w = ld_tag(qp + i * 32);
                    ok = ok && ((unsigned)(w >> 32) == epoch);
                    v[i] = (uint32_t)w;
                }
                if (__all_sync(0xffffffffu, ok)) break;
                if (lane < NWARP && nstg < NSTAGE) {
                    uint32_t done;
                    asm volatile("{\n.reg .pred p;\nmbarrier.test_wait.parity.shared::cta.b64 p, [%1], 0;\nselp.u32 %0, 1, 0, p;\n}\n"
                                 : "=r"(done) : "r"(bw + (nstg - 1) * 8) : "memory");
                    if (done) { issue_other(nstg); nstg++; }
                }
                __nanosleep(QSLEEP);
            }
            if (lane < NWARP) for (; nstg < NSTAGE; nstg++) issue_other(nstg);
#pragma unroll
            for (int i = 0; i < 8; i++) s_qw[i * 32 + lane] = v[i];
        }
        CTA_SYNC();
        int hl = lane >> 2;
        const uint32_t* qs = s_qw + (hl & 3) * 64 + (lane & 3);
#pragma unroll
        for (int ks = 0; ks < 8; ks++) {
            qa[ks][0] = hl < 4 ? qs[ks * 8] : 0u;
            qa[ks][1] = hl < 4 ? qs[ks * 8 + 4] : 0u;
        }
    }
    TS(3);
    float oacc[16][4];
#pragma unroll
    for (int j = 0; j < 16; j++) { oacc[j][0] = 0.f; oacc[j][1] = 0.f; oacc[j][2] = 0.f; oacc[j][3] = 0.f; }
    float m_run = -INFINITY, l_run = 0.f;
    const float scale = 0.08838834764831845f;
    const float LOG2E = 1.4426950408889634f;

    const int lrow = lane & 7, lmat = lane >> 3;
    const int k_row = (lmat >> 1) * 8 + lrow;
    const int k_cofs = lmat & 1;
    const int v_row = (lmat & 1) * 8 + lrow;
    const int v_cofs = lmat >> 1;

#pragma unroll
    for (int it = 0; it < NBLK; it++) {
        wov[it] = ldg_nc_v4(wo_p + (size_t)it * 16 * DM);
        if (it < 4) w1v[it] = ldg_nc_v4(w1_p + (size_t)it * 128 * FF);
        else w2v[it - 4] = ldg_nc_v4(w2_p + (size_t)(it - 4) * 4 * DM);
        const int s = it % NSTAGE;
        const uint32_t parity = (it / NSTAGE) & 1;
        const uint32_t st = ring_w + s * STAGE_BYTES;
        mbar_wait(bar_w + s * 8, parity);

        float sc[2][4];
#pragma unroll
        for (int j = 0; j < 2; j++) { sc[j][0] = 0.f; sc[j][1] = 0.f; sc[j][2] = 0.f; sc[j][3] = 0.f; }
#pragma unroll
        for (int ks = 0; ks < 8; ks++) {
            int chunk = (ks & 3) * 2 + k_cofs;
            uint32_t addr = st + (ks >> 2) * 2048 + k_row * 128 + ((chunk ^ (k_row & 7)) << 4);
            uint32_t r0, r1, r2, r3;
            ldsm_x4(addr, r0, r1, r2, r3);
            mma16816(sc[0], qa[ks][0], 0u, qa[ks][1], 0u, r0, r1);
            mma16816(sc[1], qa[ks][0], 0u, qa[ks][1], 0u, r2, r3);
        }
        float v00 = bf16r(bf16r(sc[0][0]) * scale), v01 = bf16r(bf16r(sc[0][1]) * scale);
        float v10 = bf16r(bf16r(sc[1][0]) * scale), v11 = bf16r(bf16r(sc[1][1]) * scale);
        float mx = fmaxf(fmaxf(v00, v01), fmaxf(v10, v11));
        mx = fmaxf(mx, __shfl_xor_sync(0xffffffffu, mx, 1));
        mx = fmaxf(mx, __shfl_xor_sync(0xffffffffu, mx, 2));
        float m_new = fmaxf(m_run, mx);
        float corr = exp2f((m_run - m_new) * LOG2E);
        float p00 = exp2f((v00 - m_new) * LOG2E), p01 = exp2f((v01 - m_new) * LOG2E);
        float p10 = exp2f((v10 - m_new) * LOG2E), p11 = exp2f((v11 - m_new) * LOG2E);
        l_run = l_run * corr + (p00 + p01 + p10 + p11);
        m_run = m_new;
        uint32_t pa0 = pack_bf16(p00, p01), pa2 = pack_bf16(p10, p11);
#pragma unroll
        for (int j = 0; j < 16; j++) { oacc[j][0] *= corr; oacc[j][1] *= corr; }
#pragma unroll
        for (int jj = 0; jj < 8; jj++) {
            int chunk = (jj & 3) * 2 + v_cofs;
            uint32_t addr = st + 4096 + (jj >> 2) * 2048 + v_row * 128 + ((chunk ^ (v_row & 7)) << 4);
            uint32_t r0, r1, r2, r3;
            ldsm_x4_t(addr, r0, r1, r2, r3);
            mma16816(oacc[2 * jj], pa0, 0u, pa2, 0u, r0, r1);
            mma16816(oacc[2 * jj + 1], pa0, 0u, pa2, 0u, r2, r3);
        }
        __syncwarp();
        if (lane == 0 && it + NSTAGE < NBLK) issue_stage(it + NSTAGE);
    }
    TS(4);
    l_run += __shfl_xor_sync(0xffffffffu, l_run, 1);
    l_run += __shfl_xor_sync(0xffffffffu, l_run, 2);

    CTA_SYNC();
    float* r_o = reinterpret_cast<float*>(ring);
    float* r_m = reinterpret_cast<float*>(ring + 16384);
    float* r_l = r_m + 32;
    if (lane < 16) {
        int hl = lane >> 2;
#pragma unroll
        for (int j = 0; j < 16; j++) {
            float2 v = make_float2(oacc[j][0], oacc[j][1]);
            *reinterpret_cast<float2*>(&r_o[(warp * 4 + hl) * DH + j * 8 + (lane & 3) * 2]) = v;
        }
        if ((lane & 3) == 0) { r_m[warp * 4 + hl] = m_run; r_l[warp * 4 + hl] = l_run; }
    }
    CTA_SYNC();
    {
        int hl = tid >> 6, d = (tid & 63) * 2;
        float mm = -INFINITY;
#pragma unroll
        for (int w = 0; w < NWARP; w++) mm = fmaxf(mm, r_m[w * 4 + hl]);
        float o0 = 0.f, o1 = 0.f, ll = 0.f;
#pragma unroll
        for (int w = 0; w < NWARP; w++) {
            float c = exp2f((r_m[w * 4 + hl] - mm) * LOG2E);
            float2 v = *reinterpret_cast<float2*>(&r_o[(w * 4 + hl) * DH + d]);
            o0 += c * v.x; o1 += c * v.y; ll += c * r_l[w * 4 + hl];
        }
        int pidx = (cta * 4 + hl);
        st_tag(&g_po[(size_t)pidx * DH + d], o0, epoch);
        st_tag(&g_po[(size_t)pidx * DH + d + 1], o1, epoch);
        if ((tid & 63) == 0) { st_tag(&g_pm[pidx], mm, epoch); st_tag(&g_pl[pidx], ll, epoch); }
    }
    TS(5);

    {
        int head = cta >> 2;
        int kv = head >> 2, hl = head & 3;
        {
            int bb = tid >> 7, d = tid & 127;
            int base = ((bb * 8 + kv) * NSPLIT) * 4 + hl;
            float pm[NSPLIT], pl[NSPLIT], po[NSPLIT];
            for (int tries = 0; tries < (1 << 20); tries++) {
                bool ok = true;
#pragma unroll
                for (int s = 0; s < NSPLIT; s++) {
                    unsigned long long a0 = ld_tag(&g_pm[base + s * 4]);
                    unsigned long long a1 = ld_tag(&g_pl[base + s * 4]);
                    unsigned long long a2 = ld_tag(&g_po[(size_t)(base + s * 4) * DH + d]);
                    ok = ok && ((unsigned)(a0 >> 32) == epoch) && ((unsigned)(a1 >> 32) == epoch) && ((unsigned)(a2 >> 32) == epoch);
                    pm[s] = __uint_as_float((unsigned)a0); pl[s] = __uint_as_float((unsigned)a1); po[s] = __uint_as_float((unsigned)a2);
                }
                if (ok) break;
                __nanosleep(64);
            }
            TS(6);
            float mm = -INFINITY;
#pragma unroll
            for (int s = 0; s < NSPLIT; s++) mm = fmaxf(mm, pm[s]);
            float oo = 0.f, ll = 0.f;
#pragma unroll
            for (int s = 0; s < NSPLIT; s++) {
                float c = exp2f((pm[s] - mm) * LOG2E);
                oo += c * po[s]; ll += c * pl[s];
            }
            s_vec[tid] = bf16r(oo / ll);
        }
        CTA_SYNC();
        float a[2][8];
#pragma unroll
        for (int j = 0; j < 8; j++) { a[0][j] = 0.f; a[1][j] = 0.f; }
#pragma unroll
        for (int i = 0; i < 8; i++) {
            int r = (tid >> 4) + 16 * i;
            float o0 = s_vec[r], o1 = s_vec[128 + r];
            uint32_t w[4] = {wov[i].x, wov[i].y, wov[i].z, wov[i].w};
#pragma unroll
            for (int j = 0; j < 4; j++) {
                float lo = bf_lo(w[j]), hi = bf_hi(w[j]);
                a[0][2 * j] += o0 * lo; a[0][2 * j + 1] += o0 * hi;
                a[1][2 * j] += o1 * lo; a[1][2 * j + 1] += o1 * hi;
            }
        }
#pragma unroll
        for (int j = 0; j < 8; j++) {
            a[0][j] += __shfl_xor_sync(0xffffffffu, a[0][j], 16);
            a[1][j] += __shfl_xor_sync(0xffffffffu, a[1][j], 16);
        }
        float* s_p = reinterpret_cast<float*>(ring);
        if (lane < 16) {
#pragma unroll
            for (int bb = 0; bb < 2; bb++) {
                float4* dst = reinterpret_cast<float4*>(&s_p[(warp * 2 + bb) * 128 + lane * 8]);
                dst[0] = make_float4(a[bb][0], a[bb][1], a[bb][2], a[bb][3]);
                dst[1] = make_float4(a[bb][4], a[bb][5], a[bb][6], a[bb][7]);
            }
        }
        CTA_SYNC();
        if (tid < 64) {
            int bb = tid >> 5, c4 = (tid & 31) * 4;
            float4 acc = make_float4(0.f, 0.f, 0.f, 0.f);
#pragma unroll
            for (int w = 0; w < NWARP; w++) {
                float4 v = *reinterpret_cast<float4*>(&s_p[(w * 2 + bb) * 128 + c4]);
                acc.x += v.x; acc.y += v.y; acc.z += v.z; acc.w += v.w;
            }
            red_v4(&g_attn_acc[bb * 512 + (cta & 3) * 128 + c4], acc.x, acc.y, acc.z, acc.w);
        }
    }
    TS(7);
    grid_barrier();
    TS(8);

    float h00, h01, h10, h11;
    {
        float2 aa = __ldcg(reinterpret_cast<const float2*>(&g_attn_acc[2 * tid]));
        float2 ab = __ldcg(reinterpret_cast<const float2*>(&g_attn_acc[512 + 2 * tid]));
        h00 = bf16r(bf_lo(xv0) + bf16r(aa.x)); h01 = bf16r(bf_hi(xv0) + bf16r(aa.y));
        h10 = bf16r(bf_lo(xv1) + bf16r(ab.x)); h11 = bf16r(bf_hi(xv1) + bf16r(ab.y));
        s_vec[2 * tid] = h00; s_vec[2 * tid + 1] = h01;
        s_vec[512 + 2 * tid] = h10; s_vec[512 + 2 * tid + 1] = h11;
        CTA_SYNC();
        layernorm_2x512(s_vec, s_red, tid);
        if (cta < 112) {
            float f[2][8];
#pragma unroll
            for (int j = 0; j < 8; j++) { f[0][j] = 0.f; f[1][j] = 0.f; }
#pragma unroll
            for (int i = 0; i < 4; i++) {
                int r = (tid >> 1) + 128 * i;
                float n0 = s_vec[r], n1 = s_vec[512 + r];
                uint32_t w[4] = {w1v[i].x, w1v[i].y, w1v[i].z, w1v[i].w};
#pragma unroll
                for (int j = 0; j < 4; j++) {
                    float lo = bf_lo(w[j]), hi = bf_hi(w[j]);
                    f[0][2 * j] += n0 * lo; f[0][2 * j + 1] += n0 * hi;
                    f[1][2 * j] += n1 * lo; f[1][2 * j + 1] += n1 * hi;
                }
            }
#pragma unroll
            for (int o = 2; o < 32; o <<= 1) {
#pragma unroll
                for (int j = 0; j < 8; j++) {
                    f[0][j] += __shfl_xor_sync(0xffffffffu, f[0][j], o);
                    f[1][j] += __shfl_xor_sync(0xffffffffu, f[1][j], o);
                }
            }
            float* s_fp = reinterpret_cast<float*>(ring);
            if (lane < 2) {
#pragma unroll
                for (int j = 0; j < 8; j++) {
                    s_fp[(warp * 2 + 0) * 16 + lane * 8 + j] = f[0][j];
                    s_fp[(warp * 2 + 1) * 16 + lane * 8 + j] = f[1][j];
                }
            }
            CTA_SYNC();
            if (tid < 32) {
                int bb = tid >> 4, c = tid & 15;
                float sacc = 0.f;
#pragma unroll
                for (int w = 0; w < NWARP; w++) sacc += s_fp[(w * 2 + bb) * 16 + c];
                float hh = bf16r(bf16r(sacc) + bias1);
                s_f[tid] = bf16r(gelu_tanh(hh));
            }
            CTA_SYNC();
            float a[2][8];
#pragma unroll
            for (int j = 0; j < 8; j++) { a[0][j] = 0.f; a[1][j] = 0.f; }
#pragma unroll
            for (int i = 0; i < 4; i++) {
                int r = (tid >> 6) + 4 * i;
                float f0 = s_f[r], f1 = s_f[16 + r];
                uint32_t w[4] = {w2v[i].x, w2v[i].y, w2v[i].z, w2v[i].w};
#pragma unroll
                for (int j = 0; j < 4; j++) {
                    float lo = bf_lo(w[j]), hi = bf_hi(w[j]);
                    a[0][2 * j] += f0 * lo; a[0][2 * j + 1] += f0 * hi;
                    a[1][2 * j] += f1 * lo; a[1][2 * j + 1] += f1 * hi;
                }
            }
            float* s_p = reinterpret_cast<float*>(ring) + 1024;
            {
                int g = tid >> 6, c8 = (tid & 63) * 8;
#pragma unroll
                for (int bb = 0; bb < 2; bb++) {
                    float4* dst = reinterpret_cast<float4*>(&s_p[(g * 2 + bb) * 512 + c8]);
                    dst[0] = make_float4(a[bb][0], a[bb][1], a[bb][2], a[bb][3]);
                    dst[1] = make_float4(a[bb][4], a[bb][5], a[bb][6], a[bb][7]);
                }
            }
            CTA_SYNC();
            {
                int bb = tid >> 7, c4 = (tid & 127) * 4;
                float4 acc = make_float4(0.f, 0.f, 0.f, 0.f);
#pragma unroll
                for (int g = 0; g < 4; g++) {
                    float4 v = *reinterpret_cast<float4*>(&s_p[(g * 2 + bb) * 512 + c4]);
                    acc.x += v.x; acc.y += v.y; acc.z += v.z; acc.w += v.w;
                }
                red_v4(&g_out_acc[(cta & 3) * 1024 + bb * 512 + c4], acc.x, acc.y, acc.z, acc.w);
            }
        }
    }
    TS(9);
    __shared__ unsigned s_last;
    CTA_SYNC();
    if (tid == 0) {
        __threadfence();
        unsigned old = atomicAdd(&g_done, 1u);
        s_last = ((old % NCTA) == NCTA - 1) ? 1u : 0u;
        __threadfence();
    }
    CTA_SYNC();
    if (s_last) {
        float2 oa = make_float2(0.f, 0.f), ob = make_float2(0.f, 0.f);
#pragma unroll
        for (int c = 0; c < 4; c++) {
            float2 va = __ldcg(reinterpret_cast<const float2*>(&g_out_acc[c * 1024 + 2 * tid]));
            float2 vb = __ldcg(reinterpret_cast<const float2*>(&g_out_acc[c * 1024 + 512 + 2 * tid]));
            oa.x += va.x; oa.y += va.y; ob.x += vb.x; ob.y += vb.y;
        }
        uint32_t bb = bias2;
        float bl = bf_lo(bb), bhh = bf_hi(bb);
        float r00 = h00 + bf16r(bf16r(oa.x) + bl), r01 = h01 + bf16r(bf16r(oa.y) + bhh);
        float r10 = h10 + bf16r(bf16r(ob.x) + bl), r11 = h11 + bf16r(bf16r(ob.y) + bhh);
        *reinterpret_cast<uint32_t*>(out + 2 * tid) = pack_bf16(r00, r01);
        *reinterpret_cast<uint32_t*>(out + 512 + 2 * tid) = pack_bf16(r10, r11);
        for (int i = tid; i < NB * DM; i += NTHREADS) g_attn_acc[i] = 0.f;
        for (int i = tid; i < 4 * NB * DM; i += NTHREADS) g_out_acc[i] = 0.f;
        if (tid == 0) g_epoch = epoch;
    }
    TS(10);
}

typedef CUresult (*PFN_encodeTiled)(CUtensorMap*, CUtensorMapDataType, cuuint32_t, void*, const cuuint64_t*,
                                    const cuuint64_t*, const cuuint32_t*, const cuuint32_t*, CUtensorMapInterleave,
                                    CUtensorMapSwizzle, CUtensorMapL2promotion, CUtensorMapFloatOOBfill);

}

extern "C" void kernel_launch(void* const* d_in, const int* in_sizes, int n_in, void* d_out, int out_size) {
    static PFN_encodeTiled enc = nullptr;
    if (!enc) {
        void* fn = nullptr;
        cudaDriverEntryPointQueryResult qres;
        cudaGetDriverEntryPoint("cuTensorMapEncodeTiled", &fn, cudaEnableDefault, &qres);
        enc = (PFN_encodeTiled)fn;
        cudaFuncSetAttribute(fused_kernel, cudaFuncAttributeMaxDynamicSharedMemorySize, SMEM_BYTES);
    }
    CUtensorMap mapK, mapV;
    cuuint64_t gdim[2] = {(cuuint64_t)DH, (cuuint64_t)NB * HKV * SK};
    cuuint64_t gstr[1] = {(cuuint64_t)DH * 2};
    cuuint32_t box[2] = {64, 16};
    cuuint32_t estr[2] = {1, 1};
    enc(&mapK, CU_TENSOR_MAP_DATA_TYPE_BFLOAT16, 2, d_in[1], gdim, gstr, box, estr, CU_TENSOR_MAP_INTERLEAVE_NONE,
        CU_TENSOR_MAP_SWIZZLE_128B, CU_TENSOR_MAP_L2_PROMOTION_L2_128B, CU_TENSOR_MAP_FLOAT_OOB_FILL_NONE);
    enc(&mapV, CU_TENSOR_MAP_DATA_TYPE_BFLOAT16, 2, d_in[2], gdim, gstr, box, estr, CU_TENSOR_MAP_INTERLEAVE_NONE,
        CU_TENSOR_MAP_SWIZZLE_128B, CU_TENSOR_MAP_L2_PROMOTION_L2_128B, CU_TENSOR_MAP_FLOAT_OOB_FILL_NONE);
    fused_kernel<<<NCTA, NTHREADS, SMEM_BYTES>>>(
        mapK, mapV, (const __nv_bfloat16*)d_in[0], (const __nv_bfloat16*)d_in[3], (const __nv_bfloat16*)d_in[4],
        (const __nv_bfloat16*)d_in[6], (const __nv_bfloat16*)d_in[7], (const __nv_bfloat16*)d_in[8],
        (const __nv_bfloat16*)d_in[9], (__nv_bfloat16*)d_out);
}
```
